```python
import torch

def _softmax(x, axis=-1):
    return torch.softmax(x, dim=axis)

def _gelu(x):
    return torch.nn.functional.gelu(x, approximate='tanh')

def _silu(x):
    return torch.nn.functional.silu(x)

def _sigmoid(x):
    return torch.sigmoid(x)

def _layernorm(x, axis=-1, eps=1e-05):
    m = x.mean(dim=axis, keepdim=True)
    v = x.var(dim=axis, keepdim=True, unbiased=False)
    return (x - m) / torch.sqrt(v + eps)

def _scatter_add(tgt, idx, src, axis=0):
    return tgt.clone().index_add_(axis, idx, src)

def _segment_sum(src, seg, n):
    out = torch.zeros((n,) + src.shape[1:], dtype=src.dtype)
    return out.index_add_(0, seg, src)

def _pad(x, pw):
    flat = tuple((v for pair in reversed(pw) for v in pair))
    return torch.nn.functional.pad(x, flat)
kernel_name = 'interleave_layers__sliding_local_dilated__memory_aug_recurrent_mem_tr__prompt'

def setup_inputs():

    _w = lambda a: (lambda t: t.to(torch.bfloat16) if t.is_floating_point() else t)(torch.as_tensor(a))

    def _A_setup():
        B, S, D = (1, 2048, 576)
        return {'x': _w((lambda *s: torch.randn(*s, dtype=torch.bfloat16) * 0.05)(B, S, D)), 'wqkv': _w((lambda *s: torch.randn(*s, dtype=torch.bfloat16) * 0.05)(D, 3 * D)), 'wo': _w((lambda *s: torch.randn(*s, dtype=torch.bfloat16) * 0.05)(D, D))}
    _A_in = _A_setup()

    def _B_setup():
        B, S, Dm = (1, 2048, 576)
        H, Dh = (32, 128)
        M, seg = (8, 32)
        seg = min(seg, S)
        S = S // seg * seg
        return {'x': _w((lambda *s: torch.randn(*s, dtype=torch.bfloat16) * 0.05)(B, S, Dm)), 'mem0': _w((lambda *s: torch.randn(*s, dtype=torch.bfloat16) * 0.8)(B, M, Dm)), 'Wq': _w((lambda *s: torch.randn(*s, dtype=torch.bfloat16) * 1.6)(Dm, H, Dh) * Dm ** (-0.5)), 'Wk': _w((lambda *s: torch.randn(*s, dtype=torch.bfloat16) * 1.6)(Dm, H, Dh) * Dm ** (-0.5)), 'Wv': _w((lambda *s: torch.randn(*s, dtype=torch.bfloat16) * 0.8)(Dm, H, Dh) * Dm ** (-0.5)), 'Wo': _w((lambda *s: torch.randn(*s, dtype=torch.bfloat16) * 0.8)(H, Dh, Dm) * (H * Dh) ** (-0.5)), 'seg_len': seg}
    _B_in = _B_setup()
    return {'A_x': _A_in['x'], 'A_wqkv': _A_in['wqkv'], 'A_wo': _A_in['wo'], 'B_x': _B_in['x'], 'B_mem0': _B_in['mem0'], 'B_Wq': _B_in['Wq'], 'B_Wk': _B_in['Wk'], 'B_Wv': _B_in['Wv'], 'B_Wo': _B_in['Wo'], 'B_seg_len': _B_in['seg_len']}

def reference(A_x, A_wqkv, A_wo, B_x, B_mem0, B_Wq, B_Wk, B_Wv, B_Wo, B_seg_len):

    def _A_ref(x, wqkv, wo):
        B, S, D = x.shape
        H = 32
        Dh = D // H
        W, dil = (8, 2)
        qkv = (lambda x, *d: x.permute(*d))((x @ wqkv).reshape(B, S, 3, H, Dh), 2, 0, 3, 1, 4)
        q, k, v = (qkv[0], qkv[1], qkv[2])
        scale = Dh ** (-0.5)
        pos = torch.arange(S)
        off = torch.arange(W) * dil
        idx = pos[:, None] - off[None, :]
        mask = idx >= 0
        idx_c = torch.where(mask, idx, 0).reshape(-1)
        kg = k[:, :, idx_c, :].reshape(B, H, S, W, Dh)
        vg = v[:, :, idx_c, :].reshape(B, H, S, W, Dh)
        logits = torch.einsum('bhsd,bhswd->bhsw', q, kg) * scale
        logits = torch.where(mask[None, None, :, :], logits, -1000000000.0)
        attn = _softmax(logits, axis=-1)
        o = torch.einsum('bhsw,bhswd->bhsd', attn, vg)
        return (lambda x, *d: x.permute(*d))(o, 0, 2, 1, 3).reshape(B, S, D) @ wo

    def _B_ref(x, mem0, Wq, Wk, Wv, Wo, seg_len):
        B, S, Dm = x.shape
        H, Dh = (Wq.shape[1], Wq.shape[2])
        M = mem0.shape[1]
        scale = Dh ** (-0.5)
        n_seg = S // seg_len
        L = M + seg_len
        idx = torch.arange(L)
        mask = (idx[:, None] < M) | (idx[:, None] >= idx[None, :])
        mem = mem0
        outs = []
        for s in range(n_seg):
            xs = x[:, s * seg_len:(s + 1) * seg_len, :].clone()
            h = torch.concatenate([mem, xs], axis=1)
            q = torch.einsum('btd,dhe->bhte', h, Wq)
            k = torch.einsum('btd,dhe->bhte', h, Wk)
            v = torch.einsum('btd,dhe->bhte', h, Wv)
            scores = torch.einsum('bhqe,bhke->bhqk', q, k) * scale
            scores = torch.where(mask[None, None], scores, -1000000000.0)
            p = _softmax(scores, axis=-1)
            o = torch.einsum('bhqk,bhke->bhqe', p, v)
            o = torch.einsum('bhte,hed->btd', o, Wo)
            mem = o[:, :M, :].clone()
            outs.append(o[:, M:, :])
        return torch.concatenate(outs, axis=1)
    x = A_x
    x = x + _A_ref(_layernorm(x, axis=-1), A_wqkv, A_wo)
    x = x + _B_ref(_layernorm(x, axis=-1), B_mem0, B_Wq, B_Wk, B_Wv, B_Wo, B_seg_len)
    x = x + _A_ref(_layernorm(x, axis=-1), A_wqkv, A_wo)
    x = x + _B_ref(_layernorm(x, axis=-1), B_mem0, B_Wq, B_Wk, B_Wv, B_Wo, B_seg_len)
    return x
```

```cpp
#include <cuda_runtime.h>
#include <cuda_bf16.h>
#include <stdint.h>
typedef __nv_bfloat16 bf16;
#define S_ 2048
#define D_ 576
__device__ bf16 g_xn[S_*D_], g_x1[S_*D_], g_qkv[S_*1728], g_oa[S_*D_];
__device__ bf16 g_Q[S_*4096], g_K[S_*4096], g_V[S_*4096], g_O[S_*4096];
__device__ bf16 g_mem[8*D_], g_qm[8*4096], g_km[8*4096], g_vm[8*4096], g_om[8*4096];

__global__ void k_ln(const bf16* x, bf16* y) {
  int row = blockIdx.x * 4 + (threadIdx.x >> 5), lane = threadIdx.x & 31;
  float v[18]; float s = 0;
  for (int i = 0; i < 18; i++) { v[i] = __bfloat162float(x[row*D_ + i*32 + lane]); s += v[i]; }
  for (int o = 16; o; o >>= 1) s += __shfl_xor_sync(~0u, s, o);
  float m = s / D_, q = 0;
  for (int i = 0; i < 18; i++) q += (v[i]-m)*(v[i]-m);
  for (int o = 16; o; o >>= 1) q += __shfl_xor_sync(~0u, q, o);
  float r = rsqrtf(q / D_ + 1e-5f);
  for (int i = 0; i < 18; i++) y[row*D_ + i*32 + lane] = __float2bfloat16((v[i]-m)*r);
}
__global__ void k_gemm(const bf16* A, const bf16* B, const bf16* R, bf16* C, int M, int N, int K) {
  __shared__ float sa[16][65], sb[16][65];
  int tx = threadIdx.x & 15, ty = threadIdx.x >> 4, m0 = blockIdx.y*64, n0 = blockIdx.x*64;
  float acc[4][4] = {};
  for (int k0 = 0; k0 < K; k0 += 16) {
    for (int i = threadIdx.x; i < 1024; i += 256) {
      int r = i >> 4, c = i & 15; sa[c][r] = (m0+r < M) ? __bfloat162float(A[(size_t)(m0+r)*K + k0 + c]) : 0.f;
      int kk = i >> 6, n = i & 63; sb[kk][n] = __bfloat162float(B[(size_t)(k0+kk)*N + n0 + n]);
    }
    __syncthreads();
    for (int kk = 0; kk < 16; kk++) for (int i = 0; i < 4; i++) for (int j = 0; j < 4; j++) acc[i][j] += sa[kk][ty*4+i]*sb[kk][tx*4+j];
    __syncthreads();
  }
  for (int i = 0; i < 4; i++) for (int j = 0; j < 4; j++) { int m = m0+ty*4+i, n = n0+tx*4+j; if (m < M) {
    float v = acc[i][j]; if (R) v += __bfloat162float(R[(size_t)m*N+n]); C[(size_t)m*N+n] = __float2bfloat16(v); } }
}
__global__ void k_attnA(const bf16* qkv, bf16* o) {
  int t = blockIdx.x * 4 + (threadIdx.x >> 5), h = threadIdx.x & 31;
  float q[18], l[8], mx = -1e30f;
  for (int d = 0; d < 18; d++) q[d] = __bfloat162float(qkv[t*1728 + h*18 + d]);
  for (int w = 0; w < 8; w++) { int u = t - 2*w; if (u >= 0) { float s = 0; for (int d = 0; d < 18; d++) s += q[d]*__bfloat162float(qkv[u*1728 + 576 + h*18 + d]); l[w] = s * 0.23570226f; mx = fmaxf(mx, l[w]); } }
  float sum = 0; for (int w = 0; w < 8; w++) { l[w] = (t - 2*w >= 0) ? __expf(l[w]-mx) : 0.f; sum += l[w]; }
  for (int d = 0; d < 18; d++) { float a = 0; for (int w = 0; w < 8; w++) { int u = t - 2*w; if (u >= 0) a += l[w]*__bfloat162float(qkv[u*1728 + 1152 + h*18 + d]); } o[t*D_ + h*18 + d] = __float2bfloat16(a/sum); }
}
__global__ void k_attnB(int seg) {
  int h = blockIdx.x, r = blockIdx.y, d = threadIdx.x;
  __shared__ float q[128], p[40];
  q[d] = __bfloat162float(r < 8 ? g_qm[r*4096 + h*128 + d] : g_Q[(size_t)(seg*32 + r - 8)*4096 + h*128 + d]);
  __syncthreads();
  if (d < 40) { float s = 0; const bf16* kp = d < 8 ? &g_km[d*4096 + h*128] : &g_K[(size_t)(seg*32 + d - 8)*4096 + h*128];
    for (int e = 0; e < 128; e++) s += q[e]*__bfloat162float(kp[e]); p[d] = (r < 8 || r >= d) ? s * 0.08838835f : -1e30f; }
  __syncthreads();
  float mx = -1e30f; for (int k = 0; k < 40; k++) mx = fmaxf(mx, p[k]);
  float sum = 0, a = 0;
  for (int k = 0; k < 40; k++) { float e = __expf(p[k]-mx); sum += e; a += e*__bfloat162float(k < 8 ? g_vm[k*4096 + h*128 + d] : g_V[(size_t)(seg*32 + k - 8)*4096 + h*128 + d]); }
  bf16 o = __float2bfloat16(a/sum);
  if (r < 8) g_om[r*4096 + h*128 + d] = o; else g_O[(size_t)(seg*32 + r - 8)*4096 + h*128 + d] = o;
}
template<class T> T* sym(T& s) { void* p; cudaGetSymbolAddress(&p, s); return (T*)p; }
extern "C" void kernel_launch(void* const* d_in, const int* in_sizes, int n_in, void* d_out, int out_size) {
  const bf16 *x = (const bf16*)d_in[0], *wqkv = (const bf16*)d_in[1], *wo = (const bf16*)d_in[2], *mem0 = (const bf16*)d_in[4];
  const bf16 *Wq = (const bf16*)d_in[5], *Wk = (const bf16*)d_in[6], *Wv = (const bf16*)d_in[7], *Wo = (const bf16*)d_in[8];
  bf16 *xn = (bf16*)sym(g_xn), *x1 = (bf16*)sym(g_x1), *qkv = (bf16*)sym(g_qkv), *oa = (bf16*)sym(g_oa), *Q = (bf16*)sym(g_Q), *K = (bf16*)sym(g_K), *V = (bf16*)sym(g_V), *O = (bf16*)sym(g_O);
  bf16 *mem = (bf16*)sym(g_mem), *qm = (bf16*)sym(g_qm), *km = (bf16*)sym(g_km), *vm = (bf16*)sym(g_vm), *om = (bf16*)sym(g_om);
  bf16* out = (bf16*)d_out;
  const bf16* cur = x;
  for (int l = 0; l < 2; l++) {
    k_ln<<<512,128>>>(cur, xn);
    k_gemm<<<dim3(27,32),256>>>(xn, wqkv, nullptr, qkv, S_, 1728, D_);
    k_attnA<<<512,128>>>(qkv, oa);
    k_gemm<<<dim3(9,32),256>>>(oa, wo, cur, x1, S_, D_, D_);
    k_ln<<<512,128>>>(x1, xn);
    k_gemm<<<dim3(64,32),256>>>(xn, Wq, nullptr, Q, S_, 4096, D_);
    k_gemm<<<dim3(64,32),256>>>(xn, Wk, nullptr, K, S_, 4096, D_);
    k_gemm<<<dim3(64,32),256>>>(xn, Wv, nullptr, V, S_, 4096, D_);
    for (int s = 0; s < 64; s++) {
      const bf16* m = s ? mem : mem0;
      k_gemm<<<dim3(64,1),256>>>(m, Wq, nullptr, qm, 8, 4096, D_);
      k_gemm<<<dim3(64,1),256>>>(m, Wk, nullptr, km, 8, 4096, D_);
      k_gemm<<<dim3(64,1),256>>>(m, Wv, nullptr, vm, 8, 4096, D_);
      k_attnB<<<dim3(32,40),128>>>(s);
      k_gemm<<<dim3(9,1),256>>>(om, Wo, nullptr, mem, 8, D_, 4096);
    }
    k_gemm<<<dim3(9,32),256>>>(O, Wo, x1, out, S_, D_, 4096);
    cur = out;
  }
}
```

```cpp
#include <cuda_runtime.h>
#include <cuda_bf16.h>
#include <stdint.h>
typedef __nv_bfloat16 bf16;

#define LAG 8
#define N0 2
#define N1 10
#define N2 12
#define N3 26
#define PD 500
#define PD2 800
constexpr int NSEG = 64;
constexpr int NSTEP = NSEG + LAG;
constexpr int LEAD = LAG + 2;
constexpr int ORING = 16, PRING = 16;

__device__ uint4 g_xr[4][NSEG][2304];
__device__ uint4 g_xnA[2][NSEG][2304];
__device__ uint4 g_oA[2][NSEG][2304];
__device__ uint4 g_xnB[2][NSEG][2304];
__device__ uint4 g_O[2][ORING][2][256][32];
__device__ uint4 g_P[2][PRING][7][2][36][32];
__device__ uint4 g_stat[2][NSEG][2][32];
__device__ uint4 g_acc[4][1536];
__device__ uint32_t g_fXA[2][NSEG][2][8], g_fOA[2][NSEG][2][8], g_fXB[2][NSEG][8], g_fP[2][NSEG][2][8];
__device__ uint32_t g_fO[2][NSEG][2][32];
__device__ uint32_t g_epoch;
#define TR(i)
#define GT(n, i)

#define OPAQUE(x) asm volatile("" : "+r"(x))
template<int N> __device__ __forceinline__ void pin(float* a) {
#pragma unroll
  for (int i = 0; i < N; i++) asm volatile("" : "+f"(a[i]) :: "memory");
}
constexpr uint32_t SPIN_MAX = 4000000;
__device__ __forceinline__ uint32_t smem_u32(const void* p) { return (uint32_t)__cvta_generic_to_shared(p); }
__device__ __forceinline__ void mbar_init(uint32_t mb, uint32_t n) { asm volatile("mbarrier.init.shared::cta.b64 [%0], %1;" :: "r"(mb), "r"(n) : "memory"); }
__device__ __forceinline__ void mbar_expect(uint32_t mb, uint32_t bytes) { asm volatile("mbarrier.arrive.expect_tx.shared::cta.b64 _, [%0], %1;" :: "r"(mb), "r"(bytes) : "memory"); }
__device__ __forceinline__ void mbar_arrive(uint32_t mb) { asm volatile("mbarrier.arrive.shared::cta.b64 _, [%0];" :: "r"(mb) : "memory"); }
__device__ __forceinline__ void mbar_wait(uint32_t mb, uint32_t par) {
  asm volatile("{.reg .pred p; .reg .u32 c; mov.u32 c, 0;\n"
               "W_%=: mbarrier.try_wait.parity.shared::cta.b64 p, [%0], %1; @p bra D_%=;\n"
               "add.u32 c, c, 1; setp.lt.u32 p, c, 4000000; @p bra W_%=; trap;\n"
               "D_%=: }" :: "r"(mb), "r"(par) : "memory");
}
__device__ __forceinline__ void st_async1(uint32_t a, uint32_t v, uint32_t mb) {
  asm volatile("st.async.weak.shared::cluster.mbarrier::complete_tx::bytes.b32 [%0], %1, [%2];" :: "r"(a), "r"(v), "r"(mb) : "memory");
}
__device__ __forceinline__ void st_async4(uint32_t a, uint32_t x, uint32_t y, uint32_t z, uint32_t w, uint32_t mb) {
  asm volatile("st.async.weak.shared::cluster.mbarrier::complete_tx::bytes.v4.b32 [%0], {%1,%2,%3,%4}, [%5];" :: "r"(a), "r"(x), "r"(y), "r"(z), "r"(w), "r"(mb) : "memory");
}
__device__ __forceinline__ void fence_async() { asm volatile("fence.proxy.async.shared::cta;" ::: "memory"); }
__device__ __forceinline__ void fence_gpu() { asm volatile("fence.acq_rel.gpu;" ::: "memory"); }
__device__ __forceinline__ void wg_fence() { asm volatile("wgmma.fence.sync.aligned;" ::: "memory"); }
__device__ __forceinline__ void wg_commit() { asm volatile("wgmma.commit_group.sync.aligned;" ::: "memory"); }
template<int N> __device__ __forceinline__ void wg_wait() { asm volatile("wgmma.wait_group.sync.aligned %0;" :: "n"(N) : "memory"); }
__device__ __forceinline__ uint32_t pk(float a, float b) { uint32_t r; asm("cvt.rn.bf16x2.f32 %0, %1, %2;" : "=r"(r) : "f"(b), "f"(a)); return r; }
__device__ __forceinline__ float blo(uint32_t v) { return __uint_as_float(v << 16); }
__device__ __forceinline__ float bhi(uint32_t v) { return __uint_as_float(v & 0xFFFF0000u); }
__device__ __forceinline__ float ex2(float x) { float y; asm("ex2.approx.ftz.f32 %0, %1;" : "=f"(y) : "f"(x)); return y; }
__device__ __forceinline__ float rcp(float x) { float y; asm("rcp.approx.ftz.f32 %0, %1;" : "=f"(y) : "f"(x)); return y; }
__device__ __forceinline__ uint64_t mkdesc(uint32_t addr, uint32_t lbo, uint32_t sbo) {
  return (uint64_t)((addr & 0x3FFFF) >> 4) | ((uint64_t)(lbo >> 4) << 16) | ((uint64_t)(sbo >> 4) << 32);
}
__device__ __forceinline__ void cp16(uint32_t dst, const void* src) { asm volatile("cp.async.cg.shared.global [%0], [%1], 16;" :: "r"(dst), "l"(src) : "memory"); }
__device__ __forceinline__ void cp4(uint32_t dst, const void* src) { asm volatile("cp.async.ca.shared.global [%0], [%1], 4;" :: "r"(dst), "l"(src) : "memory"); }
__device__ __forceinline__ void cp_wait_all() { asm volatile("cp.async.commit_group; cp.async.wait_group 0;" ::: "memory"); }
__device__ __forceinline__ void ldsm4(uint32_t* r, uint32_t addr) {
  asm volatile("ldmatrix.sync.aligned.m8n8.x4.shared.b16 {%0,%1,%2,%3}, [%4];" : "=r"(r[0]), "=r"(r[1]), "=r"(r[2]), "=r"(r[3]) : "r"(addr) : "memory");
}
__device__ __forceinline__ void ldsm2(uint32_t* r, uint32_t addr) {
  asm volatile("ldmatrix.sync.aligned.m8n8.x2.shared.b16 {%0,%1}, [%2];" : "=r"(r[0]), "=r"(r[1]) : "r"(addr) : "memory");
}
__device__ __forceinline__ void ldsm4t(uint32_t* r, uint32_t addr) {
  asm volatile("ldmatrix.sync.aligned.m8n8.x4.trans.shared.b16 {%0,%1,%2,%3}, [%4];" : "=r"(r[0]), "=r"(r[1]), "=r"(r[2]), "=r"(r[3]) : "r"(addr) : "memory");
}
__device__ __forceinline__ void bulk_g2s(uint32_t dst, const void* src, uint32_t bytes, uint32_t mb) {
  asm volatile("cp.async.bulk.shared::cluster.global.mbarrier::complete_tx::bytes [%0], [%1], %2, [%3];" :: "r"(dst), "l"(src), "r"(bytes), "r"(mb) : "memory");
}
__device__ __forceinline__ void bulk_s2g(void* dst, uint32_t src, uint32_t bytes) {
  asm volatile("cp.async.bulk.global.shared::cta.bulk_group [%0], [%1], %2; cp.async.bulk.commit_group;" :: "l"(dst), "r"(src), "r"(bytes) : "memory");
}
__device__ __forceinline__ uint32_t ld_acq(const uint32_t* p) { uint32_t v; asm volatile("ld.acquire.gpu.global.u32 %0, [%1];" : "=r"(v) : "l"(p) : "memory"); return v; }
__device__ __forceinline__ uint4 ld_rlx(const uint4* p) {
  uint4 v; asm volatile("ld.relaxed.gpu.global.v4.b32 {%0,%1,%2,%3}, [%4];" : "=r"(v.x), "=r"(v.y), "=r"(v.z), "=r"(v.w) : "l"(p) : "memory"); return v;
}
__device__ __forceinline__ void ld_rlx(uint32_t* r, const uint4* p) {
  asm volatile("ld.relaxed.gpu.global.v4.b32 {%0,%1,%2,%3}, [%4];" : "=r"(r[0]), "=r"(r[1]), "=r"(r[2]), "=r"(r[3]) : "l"(p) : "memory");
}
__device__ __forceinline__ void st_rlx(uint4* p, uint4 v) {
  asm volatile("st.relaxed.gpu.global.v4.b32 [%0], {%1,%2,%3,%4};" :: "l"(p), "r"(v.x), "r"(v.y), "r"(v.z), "r"(v.w) : "memory");
}
__device__ __forceinline__ void red4(uint4* p, uint32_t a, uint32_t b, uint32_t c) {
  asm volatile("red.relaxed.gpu.global.add.noftz.v4.bf16x2 [%0], {%1,%2,%3,%4};" :: "l"(p), "r"(a), "r"(b), "r"(c), "r"(0x3F80u) : "memory");
}
__device__ __forceinline__ void sts1(uint32_t a, uint32_t v) { asm volatile("st.shared.b32 [%0], %1;" :: "r"(a), "r"(v) : "memory"); }
__device__ __forceinline__ void sts4(uint32_t a, uint32_t x, uint32_t y, uint32_t z, uint32_t w) { asm volatile("st.shared.v4.b32 [%0], {%1,%2,%3,%4};" :: "r"(a), "r"(x), "r"(y), "r"(z), "r"(w) : "memory"); }
__device__ __forceinline__ void flag_wait(const uint32_t* p, uint32_t target) {
  uint32_t it = 0;
  while (ld_acq(p) != target) { if (++it > SPIN_MAX) __trap(); }
}
__device__ __forceinline__ void flag_add(uint32_t* p) {
  fence_gpu();
  __syncwarp();
  if ((threadIdx.x & 31) == 0) asm volatile("red.relaxed.gpu.global.add.u32 [%0], 1;" :: "l"(p) : "memory");
}
#define HMMA(d, a0, a1, a2, a3, b0, b1) asm volatile("mma.sync.aligned.m16n8k16.row.col.f32.bf16.bf16.f32 {%0,%1,%2,%3},{%4,%5,%6,%7},{%8,%9},{%0,%1,%2,%3};" \
  : "+f"((d)[0]), "+f"((d)[1]), "+f"((d)[2]), "+f"((d)[3]) : "r"(a0), "r"(a1), "r"(a2), "r"(a3), "r"(b0), "r"(b1))
#define HMMA8(d, a0, a1, b0) asm volatile("mma.sync.aligned.m16n8k8.row.col.f32.bf16.bf16.f32 {%0,%1,%2,%3},{%4,%5},{%6},{%0,%1,%2,%3};" \
  : "+f"((d)[0]), "+f"((d)[1]), "+f"((d)[2]), "+f"((d)[3]) : "r"(a0), "r"(a1), "r"(b0))

template<int ACC> __device__ __forceinline__ void rs16(float* d, const uint32_t* a, uint64_t b) {
  if (ACC) asm volatile("wgmma.mma_async.sync.aligned.m64n16k16.f32.bf16.bf16 {%0,%1,%2,%3,%4,%5,%6,%7},{%8,%9,%10,%11},%12,1,1,1,0;"
    : "+f"(d[0]), "+f"(d[1]), "+f"(d[2]), "+f"(d[3]), "+f"(d[4]), "+f"(d[5]), "+f"(d[6]), "+f"(d[7])
    : "r"(a[0]), "r"(a[1]), "r"(a[2]), "r"(a[3]), "l"(b));
  else asm volatile("wgmma.mma_async.sync.aligned.m64n16k16.f32.bf16.bf16 {%0,%1,%2,%3,%4,%5,%6,%7},{%8,%9,%10,%11},%12,0,1,1,0;"
    : "=f"(d[0]), "=f"(d[1]), "=f"(d[2]), "=f"(d[3]), "=f"(d[4]), "=f"(d[5]), "=f"(d[6]), "=f"(d[7])
    : "r"(a[0]), "r"(a[1]), "r"(a[2]), "r"(a[3]), "l"(b));
}

template<int ACC> __device__ __forceinline__ void rs32(float* d, const uint32_t* a, uint64_t b) {
  if (ACC) asm volatile("wgmma.mma_async.sync.aligned.m64n32k16.f32.bf16.bf16 {%0,%1,%2,%3,%4,%5,%6,%7,%8,%9,%10,%11,%12,%13,%14,%15},{%16,%17,%18,%19},%20,1,1,1,0;"
    : "+f"(d[0]), "+f"(d[1]), "+f"(d[2]), "+f"(d[3]), "+f"(d[4]), "+f"(d[5]), "+f"(d[6]), "+f"(d[7]), "+f"(d[8]), "+f"(d[9]), "+f"(d[10]), "+f"(d[11]),
      "+f"(d[12]), "+f"(d[13]), "+f"(d[14]), "+f"(d[15])
    : "r"(a[0]), "r"(a[1]), "r"(a[2]), "r"(a[3]), "l"(b));
  else asm volatile("wgmma.mma_async.sync.aligned.m64n32k16.f32.bf16.bf16 {%0,%1,%2,%3,%4,%5,%6,%7,%8,%9,%10,%11,%12,%13,%14,%15},{%16,%17,%18,%19},%20,0,1,1,0;"
    : "=f"(d[0]), "=f"(d[1]), "=f"(d[2]), "=f"(d[3]), "=f"(d[4]), "=f"(d[5]), "=f"(d[6]), "=f"(d[7]), "=f"(d[8]), "=f"(d[9]), "=f"(d[10]), "=f"(d[11]),
      "=f"(d[12]), "=f"(d[13]), "=f"(d[14]), "=f"(d[15])
    : "r"(a[0]), "r"(a[1]), "r"(a[2]), "r"(a[3]), "l"(b));
}

template<int ACC> __device__ __forceinline__ void rs64(float* d, const uint32_t* a, uint64_t b) {
  if (ACC) asm volatile("wgmma.mma_async.sync.aligned.m64n64k16.f32.bf16.bf16 {%0,%1,%2,%3,%4,%5,%6,%7,%8,%9,%10,%11,%12,%13,%14,%15,%16,%17,%18,%19,%20,%21,%22,%23,%24,%25,%26,%27,%28,%29,%30,%31},{%32,%33,%34,%35},%36,1,1,1,0;"
    : "+f"(d[0]), "+f"(d[1]), "+f"(d[2]), "+f"(d[3]), "+f"(d[4]), "+f"(d[5]), "+f"(d[6]), "+f"(d[7]), "+f"(d[8]), "+f"(d[9]), "+f"(d[10]), "+f"(d[11]),
      "+f"(d[12]), "+f"(d[13]), "+f"(d[14]), "+f"(d[15]), "+f"(d[16]), "+f"(d[17]), "+f"(d[18]), "+f"(d[19]), "+f"(d[20]), "+f"(d[21]), "+f"(d[22]), "+f"(d[23]),
      "+f"(d[24]), "+f"(d[25]), "+f"(d[26]), "+f"(d[27]), "+f"(d[28]), "+f"(d[29]), "+f"(d[30]), "+f"(d[31])
    : "r"(a[0]), "r"(a[1]), "r"(a[2]), "r"(a[3]), "l"(b));
  else asm volatile("wgmma.mma_async.sync.aligned.m64n64k16.f32.bf16.bf16 {%0,%1,%2,%3,%4,%5,%6,%7,%8,%9,%10,%11,%12,%13,%14,%15,%16,%17,%18,%19,%20,%21,%22,%23,%24,%25,%26,%27,%28,%29,%30,%31},{%32,%33,%34,%35},%36,0,1,1,0;"
    : "=f"(d[0]), "=f"(d[1]), "=f"(d[2]), "=f"(d[3]), "=f"(d[4]), "=f"(d[5]), "=f"(d[6]), "=f"(d[7]), "=f"(d[8]), "=f"(d[9]), "=f"(d[10]), "=f"(d[11]),
      "=f"(d[12]), "=f"(d[13]), "=f"(d[14]), "=f"(d[15]), "=f"(d[16]), "=f"(d[17]), "=f"(d[18]), "=f"(d[19]), "=f"(d[20]), "=f"(d[21]), "=f"(d[22]), "=f"(d[23]),
      "=f"(d[24]), "=f"(d[25]), "=f"(d[26]), "=f"(d[27]), "=f"(d[28]), "=f"(d[29]), "=f"(d[30]), "=f"(d[31])
    : "r"(a[0]), "r"(a[1]), "r"(a[2]), "r"(a[3]), "l"(b));
}

template<int ACC> __device__ __forceinline__ void ss16tn(float* d, uint64_t a, uint64_t b) {
  if (ACC) asm volatile("wgmma.mma_async.sync.aligned.m64n16k16.f32.bf16.bf16 {%0,%1,%2,%3,%4,%5,%6,%7},%8,%9,1,1,1,1,0;"
    : "+f"(d[0]), "+f"(d[1]), "+f"(d[2]), "+f"(d[3]), "+f"(d[4]), "+f"(d[5]), "+f"(d[6]), "+f"(d[7])
    : "l"(a), "l"(b));
  else asm volatile("wgmma.mma_async.sync.aligned.m64n16k16.f32.bf16.bf16 {%0,%1,%2,%3,%4,%5,%6,%7},%8,%9,0,1,1,1,0;"
    : "=f"(d[0]), "=f"(d[1]), "=f"(d[2]), "=f"(d[3]), "=f"(d[4]), "=f"(d[5]), "=f"(d[6]), "=f"(d[7])
    : "l"(a), "l"(b));
}

template<int ACC> __device__ __forceinline__ void ss32tn(float* d, uint64_t a, uint64_t b) {
  if (ACC) asm volatile("wgmma.mma_async.sync.aligned.m64n32k16.f32.bf16.bf16 {%0,%1,%2,%3,%4,%5,%6,%7,%8,%9,%10,%11,%12,%13,%14,%15},%16,%17,1,1,1,1,0;"
    : "+f"(d[0]), "+f"(d[1]), "+f"(d[2]), "+f"(d[3]), "+f"(d[4]), "+f"(d[5]), "+f"(d[6]), "+f"(d[7]), "+f"(d[8]), "+f"(d[9]), "+f"(d[10]), "+f"(d[11]),
      "+f"(d[12]), "+f"(d[13]), "+f"(d[14]), "+f"(d[15])
    : "l"(a), "l"(b));
  else asm volatile("wgmma.mma_async.sync.aligned.m64n32k16.f32.bf16.bf16 {%0,%1,%2,%3,%4,%5,%6,%7,%8,%9,%10,%11,%12,%13,%14,%15},%16,%17,0,1,1,1,0;"
    : "=f"(d[0]), "=f"(d[1]), "=f"(d[2]), "=f"(d[3]), "=f"(d[4]), "=f"(d[5]), "=f"(d[6]), "=f"(d[7]), "=f"(d[8]), "=f"(d[9]), "=f"(d[10]), "=f"(d[11]),
      "=f"(d[12]), "=f"(d[13]), "=f"(d[14]), "=f"(d[15])
    : "l"(a), "l"(b));
}

template<int ACC> __device__ __forceinline__ void ss40tt(float* d, uint64_t a, uint64_t b) {
  if (ACC) asm volatile("wgmma.mma_async.sync.aligned.m64n40k16.f32.bf16.bf16 {%0,%1,%2,%3,%4,%5,%6,%7,%8,%9,%10,%11,%12,%13,%14,%15,%16,%17,%18,%19},%20,%21,1,1,1,1,1;"
    : "+f"(d[0]), "+f"(d[1]), "+f"(d[2]), "+f"(d[3]), "+f"(d[4]), "+f"(d[5]), "+f"(d[6]), "+f"(d[7]), "+f"(d[8]), "+f"(d[9]), "+f"(d[10]), "+f"(d[11]),
      "+f"(d[12]), "+f"(d[13]), "+f"(d[14]), "+f"(d[15]), "+f"(d[16]), "+f"(d[17]), "+f"(d[18]), "+f"(d[19])
    : "l"(a), "l"(b));
  else asm volatile("wgmma.mma_async.sync.aligned.m64n40k16.f32.bf16.bf16 {%0,%1,%2,%3,%4,%5,%6,%7,%8,%9,%10,%11,%12,%13,%14,%15,%16,%17,%18,%19},%20,%21,0,1,1,1,1;"
    : "=f"(d[0]), "=f"(d[1]), "=f"(d[2]), "=f"(d[3]), "=f"(d[4]), "=f"(d[5]), "=f"(d[6]), "=f"(d[7]), "=f"(d[8]), "=f"(d[9]), "=f"(d[10]), "=f"(d[11]),
      "=f"(d[12]), "=f"(d[13]), "=f"(d[14]), "=f"(d[15]), "=f"(d[16]), "=f"(d[17]), "=f"(d[18]), "=f"(d[19])
    : "l"(a), "l"(b));
}

template<int ACC> __device__ __forceinline__ void rs144t(float* d, const uint32_t* a, uint64_t b) {
  if (ACC) asm volatile("wgmma.mma_async.sync.aligned.m64n144k16.f32.bf16.bf16 {%0,%1,%2,%3,%4,%5,%6,%7,%8,%9,%10,%11,%12,%13,%14,%15,%16,%17,%18,%19,%20,%21,%22,%23,%24,%25,%26,%27,%28,%29,%30,%31,%32,%33,%34,%35,%36,%37,%38,%39,%40,%41,%42,%43,%44,%45,%46,%47,%48,%49,%50,%51,%52,%53,%54,%55,%56,%57,%58,%59,%60,%61,%62,%63,%64,%65,%66,%67,%68,%69,%70,%71},{%72,%73,%74,%75},%76,1,1,1,1;"
    : "+f"(d[0]), "+f"(d[1]), "+f"(d[2]), "+f"(d[3]), "+f"(d[4]), "+f"(d[5]), "+f"(d[6]), "+f"(d[7]), "+f"(d[8]), "+f"(d[9]), "+f"(d[10]), "+f"(d[11]),
      "+f"(d[12]), "+f"(d[13]), "+f"(d[14]), "+f"(d[15]), "+f"(d[16]), "+f"(d[17]), "+f"(d[18]), "+f"(d[19]), "+f"(d[20]), "+f"(d[21]), "+f"(d[22]), "+f"(d[23]),
      "+f"(d[24]), "+f"(d[25]), "+f"(d[26]), "+f"(d[27]), "+f"(d[28]), "+f"(d[29]), "+f"(d[30]), "+f"(d[31]), "+f"(d[32]), "+f"(d[33]), "+f"(d[34]), "+f"(d[35]),
      "+f"(d[36]), "+f"(d[37]), "+f"(d[38]), "+f"(d[39]), "+f"(d[40]), "+f"(d[41]), "+f"(d[42]), "+f"(d[43]), "+f"(d[44]), "+f"(d[45]), "+f"(d[46]), "+f"(d[47]),
      "+f"(d[48]), "+f"(d[49]), "+f"(d[50]), "+f"(d[51]), "+f"(d[52]), "+f"(d[53]), "+f"(d[54]), "+f"(d[55]), "+f"(d[56]), "+f"(d[57]), "+f"(d[58]), "+f"(d[59]),
      "+f"(d[60]), "+f"(d[61]), "+f"(d[62]), "+f"(d[63]), "+f"(d[64]), "+f"(d[65]), "+f"(d[66]), "+f"(d[67]), "+f"(d[68]), "+f"(d[69]), "+f"(d[70]), "+f"(d[71])
    : "r"(a[0]), "r"(a[1]), "r"(a[2]), "r"(a[3]), "l"(b));
  else asm volatile("wgmma.mma_async.sync.aligned.m64n144k16.f32.bf16.bf16 {%0,%1,%2,%3,%4,%5,%6,%7,%8,%9,%10,%11,%12,%13,%14,%15,%16,%17,%18,%19,%20,%21,%22,%23,%24,%25,%26,%27,%28,%29,%30,%31,%32,%33,%34,%35,%36,%37,%38,%39,%40,%41,%42,%43,%44,%45,%46,%47,%48,%49,%50,%51,%52,%53,%54,%55,%56,%57,%58,%59,%60,%61,%62,%63,%64,%65,%66,%67,%68,%69,%70,%71},{%72,%73,%74,%75},%76,0,1,1,1;"
    : "=f"(d[0]), "=f"(d[1]), "=f"(d[2]), "=f"(d[3]), "=f"(d[4]), "=f"(d[5]), "=f"(d[6]), "=f"(d[7]), "=f"(d[8]), "=f"(d[9]), "=f"(d[10]), "=f"(d[11]),
      "=f"(d[12]), "=f"(d[13]), "=f"(d[14]), "=f"(d[15]), "=f"(d[16]), "=f"(d[17]), "=f"(d[18]), "=f"(d[19]), "=f"(d[20]), "=f"(d[21]), "=f"(d[22]), "=f"(d[23]),
      "=f"(d[24]), "=f"(d[25]), "=f"(d[26]), "=f"(d[27]), "=f"(d[28]), "=f"(d[29]), "=f"(d[30]), "=f"(d[31]), "=f"(d[32]), "=f"(d[33]), "=f"(d[34]), "=f"(d[35]),
      "=f"(d[36]), "=f"(d[37]), "=f"(d[38]), "=f"(d[39]), "=f"(d[40]), "=f"(d[41]), "=f"(d[42]), "=f"(d[43]), "=f"(d[44]), "=f"(d[45]), "=f"(d[46]), "=f"(d[47]),
      "=f"(d[48]), "=f"(d[49]), "=f"(d[50]), "=f"(d[51]), "=f"(d[52]), "=f"(d[53]), "=f"(d[54]), "=f"(d[55]), "=f"(d[56]), "=f"(d[57]), "=f"(d[58]), "=f"(d[59]),
      "=f"(d[60]), "=f"(d[61]), "=f"(d[62]), "=f"(d[63]), "=f"(d[64]), "=f"(d[65]), "=f"(d[66]), "=f"(d[67]), "=f"(d[68]), "=f"(d[69]), "=f"(d[70]), "=f"(d[71])
    : "r"(a[0]), "r"(a[1]), "r"(a[2]), "r"(a[3]), "l"(b));
}

template<int ACC> __device__ __forceinline__ void rs168t(float* d, const uint32_t* a, uint64_t b) {
  if (ACC) asm volatile("wgmma.mma_async.sync.aligned.m64n168k16.f32.bf16.bf16 {%0,%1,%2,%3,%4,%5,%6,%7,%8,%9,%10,%11,%12,%13,%14,%15,%16,%17,%18,%19,%20,%21,%22,%23,%24,%25,%26,%27,%28,%29,%30,%31,%32,%33,%34,%35,%36,%37,%38,%39,%40,%41,%42,%43,%44,%45,%46,%47,%48,%49,%50,%51,%52,%53,%54,%55,%56,%57,%58,%59,%60,%61,%62,%63,%64,%65,%66,%67,%68,%69,%70,%71,%72,%73,%74,%75,%76,%77,%78,%79,%80,%81,%82,%83},{%84,%85,%86,%87},%88,1,1,1,1;"
    : "+f"(d[0]), "+f"(d[1]), "+f"(d[2]), "+f"(d[3]), "+f"(d[4]), "+f"(d[5]), "+f"(d[6]), "+f"(d[7]), "+f"(d[8]), "+f"(d[9]), "+f"(d[10]), "+f"(d[11]),
      "+f"(d[12]), "+f"(d[13]), "+f"(d[14]), "+f"(d[15]), "+f"(d[16]), "+f"(d[17]), "+f"(d[18]), "+f"(d[19]), "+f"(d[20]), "+f"(d[21]), "+f"(d[22]), "+f"(d[23]),
      "+f"(d[24]), "+f"(d[25]), "+f"(d[26]), "+f"(d[27]), "+f"(d[28]), "+f"(d[29]), "+f"(d[30]), "+f"(d[31]), "+f"(d[32]), "+f"(d[33]), "+f"(d[34]), "+f"(d[35]),
      "+f"(d[36]), "+f"(d[37]), "+f"(d[38]), "+f"(d[39]), "+f"(d[40]), "+f"(d[41]), "+f"(d[42]), "+f"(d[43]), "+f"(d[44]), "+f"(d[45]), "+f"(d[46]), "+f"(d[47]),
      "+f"(d[48]), "+f"(d[49]), "+f"(d[50]), "+f"(d[51]), "+f"(d[52]), "+f"(d[53]), "+f"(d[54]), "+f"(d[55]), "+f"(d[56]), "+f"(d[57]), "+f"(d[58]), "+f"(d[59]),
      "+f"(d[60]), "+f"(d[61]), "+f"(d[62]), "+f"(d[63]), "+f"(d[64]), "+f"(d[65]), "+f"(d[66]), "+f"(d[67]), "+f"(d[68]), "+f"(d[69]), "+f"(d[70]), "+f"(d[71]),
      "+f"(d[72]), "+f"(d[73]), "+f"(d[74]), "+f"(d[75]), "+f"(d[76]), "+f"(d[77]), "+f"(d[78]), "+f"(d[79]), "+f"(d[80]), "+f"(d[81]), "+f"(d[82]), "+f"(d[83])
    : "r"(a[0]), "r"(a[1]), "r"(a[2]), "r"(a[3]), "l"(b));
  else asm volatile("wgmma.mma_async.sync.aligned.m64n168k16.f32.bf16.bf16 {%0,%1,%2,%3,%4,%5,%6,%7,%8,%9,%10,%11,%12,%13,%14,%15,%16,%17,%18,%19,%20,%21,%22,%23,%24,%25,%26,%27,%28,%29,%30,%31,%32,%33,%34,%35,%36,%37,%38,%39,%40,%41,%42,%43,%44,%45,%46,%47,%48,%49,%50,%51,%52,%53,%54,%55,%56,%57,%58,%59,%60,%61,%62,%63,%64,%65,%66,%67,%68,%69,%70,%71,%72,%73,%74,%75,%76,%77,%78,%79,%80,%81,%82,%83},{%84,%85,%86,%87},%88,0,1,1,1;"
    : "=f"(d[0]), "=f"(d[1]), "=f"(d[2]), "=f"(d[3]), "=f"(d[4]), "=f"(d[5]), "=f"(d[6]), "=f"(d[7]), "=f"(d[8]), "=f"(d[9]), "=f"(d[10]), "=f"(d[11]),
      "=f"(d[12]), "=f"(d[13]), "=f"(d[14]), "=f"(d[15]), "=f"(d[16]), "=f"(d[17]), "=f"(d[18]), "=f"(d[19]), "=f"(d[20]), "=f"(d[21]), "=f"(d[22]), "=f"(d[23]),
      "=f"(d[24]), "=f"(d[25]), "=f"(d[26]), "=f"(d[27]), "=f"(d[28]), "=f"(d[29]), "=f"(d[30]), "=f"(d[31]), "=f"(d[32]), "=f"(d[33]), "=f"(d[34]), "=f"(d[35]),
      "=f"(d[36]), "=f"(d[37]), "=f"(d[38]), "=f"(d[39]), "=f"(d[40]), "=f"(d[41]), "=f"(d[42]), "=f"(d[43]), "=f"(d[44]), "=f"(d[45]), "=f"(d[46]), "=f"(d[47]),
      "=f"(d[48]), "=f"(d[49]), "=f"(d[50]), "=f"(d[51]), "=f"(d[52]), "=f"(d[53]), "=f"(d[54]), "=f"(d[55]), "=f"(d[56]), "=f"(d[57]), "=f"(d[58]), "=f"(d[59]),
      "=f"(d[60]), "=f"(d[61]), "=f"(d[62]), "=f"(d[63]), "=f"(d[64]), "=f"(d[65]), "=f"(d[66]), "=f"(d[67]), "=f"(d[68]), "=f"(d[69]), "=f"(d[70]), "=f"(d[71]),
      "=f"(d[72]), "=f"(d[73]), "=f"(d[74]), "=f"(d[75]), "=f"(d[76]), "=f"(d[77]), "=f"(d[78]), "=f"(d[79]), "=f"(d[80]), "=f"(d[81]), "=f"(d[82]), "=f"(d[83])
    : "r"(a[0]), "r"(a[1]), "r"(a[2]), "r"(a[3]), "l"(b));
}

template<int ACC> __device__ __forceinline__ void rs192t(float* d, const uint32_t* a, uint64_t b) {
  if (ACC) asm volatile("wgmma.mma_async.sync.aligned.m64n192k16.f32.bf16.bf16 {%0,%1,%2,%3,%4,%5,%6,%7,%8,%9,%10,%11,%12,%13,%14,%15,%16,%17,%18,%19,%20,%21,%22,%23,%24,%25,%26,%27,%28,%29,%30,%31,%32,%33,%34,%35,%36,%37,%38,%39,%40,%41,%42,%43,%44,%45,%46,%47,%48,%49,%50,%51,%52,%53,%54,%55,%56,%57,%58,%59,%60,%61,%62,%63,%64,%65,%66,%67,%68,%69,%70,%71,%72,%73,%74,%75,%76,%77,%78,%79,%80,%81,%82,%83,%84,%85,%86,%87,%88,%89,%90,%91,%92,%93,%94,%95},{%96,%97,%98,%99},%100,1,1,1,1;"
    : "+f"(d[0]), "+f"(d[1]), "+f"(d[2]), "+f"(d[3]), "+f"(d[4]), "+f"(d[5]), "+f"(d[6]), "+f"(d[7]), "+f"(d[8]), "+f"(d[9]), "+f"(d[10]), "+f"(d[11]),
      "+f"(d[12]), "+f"(d[13]), "+f"(d[14]), "+f"(d[15]), "+f"(d[16]), "+f"(d[17]), "+f"(d[18]), "+f"(d[19]), "+f"(d[20]), "+f"(d[21]), "+f"(d[22]), "+f"(d[23]),
      "+f"(d[24]), "+f"(d[25]), "+f"(d[26]), "+f"(d[27]), "+f"(d[28]), "+f"(d[29]), "+f"(d[30]), "+f"(d[31]), "+f"(d[32]), "+f"(d[33]), "+f"(d[34]), "+f"(d[35]),
      "+f"(d[36]), "+f"(d[37]), "+f"(d[38]), "+f"(d[39]), "+f"(d[40]), "+f"(d[41]), "+f"(d[42]), "+f"(d[43]), "+f"(d[44]), "+f"(d[45]), "+f"(d[46]), "+f"(d[47]),
      "+f"(d[48]), "+f"(d[49]), "+f"(d[50]), "+f"(d[51]), "+f"(d[52]), "+f"(d[53]), "+f"(d[54]), "+f"(d[55]), "+f"(d[56]), "+f"(d[57]), "+f"(d[58]), "+f"(d[59]),
      "+f"(d[60]), "+f"(d[61]), "+f"(d[62]), "+f"(d[63]), "+f"(d[64]), "+f"(d[65]), "+f"(d[66]), "+f"(d[67]), "+f"(d[68]), "+f"(d[69]), "+f"(d[70]), "+f"(d[71]),
      "+f"(d[72]), "+f"(d[73]), "+f"(d[74]), "+f"(d[75]), "+f"(d[76]), "+f"(d[77]), "+f"(d[78]), "+f"(d[79]), "+f"(d[80]), "+f"(d[81]), "+f"(d[82]), "+f"(d[83]),
      "+f"(d[84]), "+f"(d[85]), "+f"(d[86]), "+f"(d[87]), "+f"(d[88]), "+f"(d[89]), "+f"(d[90]), "+f"(d[91]), "+f"(d[92]), "+f"(d[93]), "+f"(d[94]), "+f"(d[95])
    : "r"(a[0]), "r"(a[1]), "r"(a[2]), "r"(a[3]), "l"(b));
  else asm volatile("wgmma.mma_async.sync.aligned.m64n192k16.f32.bf16.bf16 {%0,%1,%2,%3,%4,%5,%6,%7,%8,%9,%10,%11,%12,%13,%14,%15,%16,%17,%18,%19,%20,%21,%22,%23,%24,%25,%26,%27,%28,%29,%30,%31,%32,%33,%34,%35,%36,%37,%38,%39,%40,%41,%42,%43,%44,%45,%46,%47,%48,%49,%50,%51,%52,%53,%54,%55,%56,%57,%58,%59,%60,%61,%62,%63,%64,%65,%66,%67,%68,%69,%70,%71,%72,%73,%74,%75,%76,%77,%78,%79,%80,%81,%82,%83,%84,%85,%86,%87,%88,%89,%90,%91,%92,%93,%94,%95},{%96,%97,%98,%99},%100,0,1,1,1;"
    : "=f"(d[0]), "=f"(d[1]), "=f"(d[2]), "=f"(d[3]), "=f"(d[4]), "=f"(d[5]), "=f"(d[6]), "=f"(d[7]), "=f"(d[8]), "=f"(d[9]), "=f"(d[10]), "=f"(d[11]),
      "=f"(d[12]), "=f"(d[13]), "=f"(d[14]), "=f"(d[15]), "=f"(d[16]), "=f"(d[17]), "=f"(d[18]), "=f"(d[19]), "=f"(d[20]), "=f"(d[21]), "=f"(d[22]), "=f"(d[23]),
      "=f"(d[24]), "=f"(d[25]), "=f"(d[26]), "=f"(d[27]), "=f"(d[28]), "=f"(d[29]), "=f"(d[30]), "=f"(d[31]), "=f"(d[32]), "=f"(d[33]), "=f"(d[34]), "=f"(d[35]),
      "=f"(d[36]), "=f"(d[37]), "=f"(d[38]), "=f"(d[39]), "=f"(d[40]), "=f"(d[41]), "=f"(d[42]), "=f"(d[43]), "=f"(d[44]), "=f"(d[45]), "=f"(d[46]), "=f"(d[47]),
      "=f"(d[48]), "=f"(d[49]), "=f"(d[50]), "=f"(d[51]), "=f"(d[52]), "=f"(d[53]), "=f"(d[54]), "=f"(d[55]), "=f"(d[56]), "=f"(d[57]), "=f"(d[58]), "=f"(d[59]),
      "=f"(d[60]), "=f"(d[61]), "=f"(d[62]), "=f"(d[63]), "=f"(d[64]), "=f"(d[65]), "=f"(d[66]), "=f"(d[67]), "=f"(d[68]), "=f"(d[69]), "=f"(d[70]), "=f"(d[71]),
      "=f"(d[72]), "=f"(d[73]), "=f"(d[74]), "=f"(d[75]), "=f"(d[76]), "=f"(d[77]), "=f"(d[78]), "=f"(d[79]), "=f"(d[80]), "=f"(d[81]), "=f"(d[82]), "=f"(d[83]),
      "=f"(d[84]), "=f"(d[85]), "=f"(d[86]), "=f"(d[87]), "=f"(d[88]), "=f"(d[89]), "=f"(d[90]), "=f"(d[91]), "=f"(d[92]), "=f"(d[93]), "=f"(d[94]), "=f"(d[95])
    : "r"(a[0]), "r"(a[1]), "r"(a[2]), "r"(a[3]), "l"(b));
}

constexpr uint32_t H_XR = 0, H_XSLOT = 36864, H_MEM = 110592, H_QB = 129024, H_KB = 139264, H_VB = 149504,
                   H_WO = 159872, H_OS = 209024, H_WL = 217216, H_BAR = 229504, H_TRC = 229760;
constexpr uint32_t H_SMEM = 229760;
constexpr int KR = 33;
constexpr uint32_t B_MEM = 0, B_XF = 32, B_XE = 56, B_QK = 80, B_V = 88, B_OM = 96, B_W2 = 104, B_W3 = 112;

__device__ __forceinline__ bool act(int L, int s) { return (uint32_t)(s - L * LAG) < (uint32_t)NSEG; }

template<int K0, int K1> __device__ __forceinline__ void tok_steps(float* acc, const uint32_t* w, uint32_t xaddr, uint64_t wl) {
  const uint64_t d = mkdesc(xaddr, 512, 128);
#pragma unroll
  for (int kk = K0; kk < K1; kk++) {
    if (kk == 0) rs32<0>(acc, &w[0], d); else if (kk < KR) rs32<1>(acc, &w[kk * 4], d + kk * 64); else ss32tn<1>(acc, wl + (kk - KR) * 16, d + kk * 64);
  }
}
__device__ __forceinline__ void send1(uint32_t v, uint32_t dst, uint32_t mb, bool on, bool local) {
  asm volatile("{.reg .pred p, q; setp.ne.u32 p, %3, 0; setp.ne.u32 q, %4, 0;\n"
               "@p st.shared.b32 [%0], %1;\n"
               "@q st.async.weak.shared::cluster.mbarrier::complete_tx::bytes.b32 [%0], %1, [%2];}"
               :: "r"(dst), "r"(v), "r"(mb), "r"((uint32_t)(on && local)), "r"((uint32_t)(on && !local)) : "memory");
}
__device__ __forceinline__ void x_load(uint32_t sb, uint32_t slot, uint32_t par, int L, int s, uint32_t target) {
  mbar_wait(sb + H_BAR + B_XE + slot * 8, par ^ 1);
  if (act(L, s)) {
    const int seg = s - L * LAG;
    flag_wait(&g_fXB[L][seg][0], target);
    asm volatile("fence.proxy.async.global;" ::: "memory");
    mbar_expect(sb + H_BAR + B_XF + slot * 8, 36864);
    bulk_g2s(sb + H_XR + slot * H_XSLOT, &g_xnB[L][seg][0], 36864, sb + H_BAR + B_XF + slot * 8);
  } else {
    mbar_arrive(sb + H_BAR + B_XF + slot * 8);
  }
}

__global__ void __cluster_dims__(3, 1, 1) __launch_bounds__(384, 1)
h_kernel(const bf16* __restrict__ Wq, const bf16* __restrict__ Wk, const bf16* __restrict__ Wv, const bf16* __restrict__ Wo, const bf16* __restrict__ mem0) {
  extern __shared__ __align__(1024) uint8_t smraw[];
  const uint32_t sb = smem_u32(smraw);
  const int h = blockIdx.x / 3, j = blockIdx.x % 3;
  const int tid = threadIdx.x, lane = tid & 31, w = __shfl_sync(~0u, (tid >> 5) & 3, 0), wg = __shfl_sync(~0u, tid >> 7, 0);
  asm volatile("griddepcontrol.launch_dependents;");
  const uint32_t epoch = *(volatile uint32_t*)&g_epoch;
  const int LF = (j == 0), LS = 1 - LF;
  {
    const bf16* W = (j == 0 ? Wq : j == 1 ? Wk : Wv) + h * 128;
    for (int i = tid; i < 576 * 16; i += 384) {
      const int k = i >> 4, c = i & 15;
      cp16(k < KR * 16 ? sb + c * 9232 + k * 16 : sb + H_WL + c * 768 + (k - KR * 16) * 16, W + (size_t)k * 4096 + c * 8);
    }
    const bf16* Wh = Wo + (size_t)h * 128 * 576;
    for (int i = tid; i < 128 * 24; i += 384) {
      const int d = i / 24, ntl = i % 24;
      const int p = 36 * ((ntl / 3) & 1) + 12 * j + 3 * (ntl / 6) + ntl % 3;
      const int slot = (d & 96) + ((d >> 1) & 3) * 8 + ((d >> 3) & 3) * 2 + (d & 1);
      cp16(sb + H_WO + ntl * 2048 + slot * 16, Wh + d * 576 + p * 8);
    }
    if (tid == 0) {
      for (int c = 0; c < 2; c++) mbar_init(sb + H_BAR + B_MEM + c * 8, 4);
      for (int c = 0; c < 3; c++) { mbar_init(sb + H_BAR + B_XF + c * 8, 1); mbar_init(sb + H_BAR + B_XE + c * 8, 8); }
      mbar_init(sb + H_BAR + B_QK, 9); mbar_init(sb + H_BAR + B_V, 1); mbar_init(sb + H_BAR + B_OM, j < 2 ? 2 : 1);
      mbar_init(sb + H_BAR + B_W2, 4); mbar_init(sb + H_BAR + B_W3, 4);
      mbar_expect(sb + H_BAR + B_QK, 10240); mbar_expect(sb + H_BAR + B_V, 10240); mbar_expect(sb + H_BAR + B_OM, j == 0 ? 0 : 2048);
      asm volatile("fence.mbarrier_init.release.cluster;" ::: "memory");
    }
    cp_wait_all();
    fence_async();
    __syncthreads();
  }
  if (wg < 2) {
    asm volatile("setmaxnreg.inc.sync.aligned.u32 192;");
    uint32_t wr[KR * 4];
    {
      const uint32_t a = sb + (wg * 8 + w * 2 + ((lane >> 3) & 1)) * 9232 + ((lane >> 4) * 8 + (lane & 7)) * 16;
#pragma unroll
      for (int kk = 0; kk < KR; kk++) ldsm4t(&wr[kk * 4], a + kk * 256);
    }
    asm volatile("bar.sync 1, 384;" ::: "memory");
    asm volatile("barrier.cluster.arrive.release.aligned; barrier.cluster.wait.acquire.aligned;" ::: "memory");
    const uint32_t boff = (sb & 0xFFFFFF) + (j == 0 ? H_QB : j == 1 ? H_KB : H_VB) + (wg * 8 + w * 2) * 640 + lane * 4;
    const uint32_t mbo = (sb & 0xFFFFFF) + H_BAR + (j == 2 ? B_V : B_QK);
    const uint32_t dstF = boff + ((uint32_t)LF << 24), mbF = mbo + ((uint32_t)LF << 24);
#define dstS (dstF ^ (1u << 24))
#define mbS (mbF ^ (1u << 24))
    const uint64_t wl = mkdesc(sb + H_WL + wg * 6144, 128, 768);
    uint32_t pb[8];
    {
      float acc[16];
      mbar_wait(sb + H_BAR + B_XF + LF * 8, 0);
      wg_fence(); tok_steps<0, 36>(acc, wr, sb + H_XR + LF * H_XSLOT, wl); wg_commit(); wg_wait<0>(); pin<16>(acc);
      if (lane == 0) { mbar_arrive(sb + H_BAR + B_XE); mbar_arrive(sb + H_BAR + B_XE + 8); }
#pragma unroll
      for (int i = 0; i < 8; i++) { pb[i] = pk(acc[2 * i], acc[2 * i + 1]); send1(pb[i], dstF + ((i & 1) * 5 + (i >> 1)) * 128, mbF, j != 0, false); }
    }
    uint32_t xs = 2, xp = 0;
    for (int s = 0; s < NSTEP; s++) {
      const uint64_t md = mkdesc(sb + H_MEM, 256, 128);
      float accA[16], accB[16], accM[8];
      const uint32_t xa = sb + H_XR + xs * H_XSLOT;
      const bool aS = act(LS, s);
#pragma unroll
      for (int c = 0; c < 2; c++) {
        if (s > 0) mbar_wait(sb + H_BAR + B_MEM + c * 8, (s - 1) & 1);
        if (wg == 0) { if (c == 0) { TR(0); } else { TR(6); } }
        fence_async();
        wg_fence();
#pragma unroll
        for (int kk = 18 * c; kk < 18 * c + 18; kk++) {
          if (kk == 0) rs16<0>(accM, &wr[0], md); else if (kk < KR) rs16<1>(accM, &wr[kk * 4], md + kk * 32); else ss16tn<1>(accM, wl + (kk - KR) * 16, md + kk * 32);
          if (kk >= 2 && kk < 18 && (kk & 1) == 0) { send1(pb[kk / 2 - 1], dstS + (((kk / 2 - 1) & 1) * 5 + ((kk / 2 - 1) >> 1)) * 128, mbS, aS, j < 2); wg_fence(); }
        }
        wg_commit();
      }
      wg_wait<0>(); pin<8>(accM);
      TR(1 + wg * 4);
      {
        const uint32_t m0 = pk(accM[0], accM[1]), m1 = pk(accM[2], accM[3]), m2 = pk(accM[4], accM[5]), m3 = pk(accM[6], accM[7]);
        if (act(LF, s)) { st_async1(dstF + 4 * 128, LF ? m2 : m0, mbF); st_async1(dstF + 9 * 128, LF ? m3 : m1, mbF); }
        send1(LF ? m0 : m2, dstS + 4 * 128, mbS, aS, j < 2); send1(LF ? m1 : m3, dstS + 9 * 128, mbS, aS, j < 2);
        __syncwarp();
        if (aS && j < 2 && lane == 0) mbar_arrive(mbS);
      }
      if (s == NSTEP - 1) break;
      mbar_wait(sb + H_BAR + B_XF + xs * 8, xp);
      wg_fence(); tok_steps<0, N1>(accA, wr, xa, wl);
      wg_commit();
      const uint32_t xsA = xs;
      if (++xs == 3) { xs = 0; xp ^= 1; }
      if (tid == 32) x_load(sb, xs, xp, LS, s + 1, (epoch + 1) * 8);
      __syncwarp();
      mbar_wait(sb + H_BAR + B_W2, s & 1);
      wg_fence(); tok_steps<N1, N1 + N2>(accA, wr, xa, wl);
      wg_commit();
      mbar_wait(sb + H_BAR + B_W3, s & 1);
      if (wg == 0) { TR(2); }
      wg_fence(); tok_steps<N1 + N2, 36>(accA, wr, xa, wl);
      wg_commit();
      mbar_wait(sb + H_BAR + B_XF + xs * 8, xp);
      wg_fence(); tok_steps<0, N3>(accB, wr, sb + H_XR + xs * H_XSLOT, wl);
      wg_commit();
      wg_wait<1>(); pin<16>(accA);
      if (lane == 0) mbar_arrive(sb + H_BAR + B_XE + xsA * 8);
      {
        const uint64_t d = mkdesc(sb + H_XR + xs * H_XSLOT, 512, 128);
        const bool aF = act(LF, s + 1);
        wg_fence();
#pragma unroll
        for (int kk = N3; kk < 36; kk++) {
          if (kk < KR) rs32<1>(accB, &wr[kk * 4], d + kk * 64); else ss32tn<1>(accB, wl + (kk - KR) * 16, d + kk * 64);
          const int i = kk - N3;
          if (i < 8) { send1(pk(accA[2 * i], accA[2 * i + 1]), dstF + ((i & 1) * 5 + (i >> 1)) * 128, mbF, aF, false); wg_fence(); }
        }
      }
      wg_commit();
      wg_wait<0>(); pin<16>(accB);
      if (wg == 0) { TR(3); }
#pragma unroll
      for (int i = 0; i < 8; i++) pb[i] = pk(accB[2 * i], accB[2 * i + 1]);
      if (lane == 0) mbar_arrive(sb + H_BAR + B_XE + xs * 8);
      if (++xs == 3) { xs = 0; xp ^= 1; }
    }
    asm volatile("barrier.cluster.arrive.release.aligned; barrier.cluster.wait.acquire.aligned;" ::: "memory");
  } else {
    asm volatile("setmaxnreg.dec.sync.aligned.u32 120;");
    const int t = tid - 256;
    asm volatile("bar.sync 1, 384;" ::: "memory");
    for (int i = t; i < 72 * 16; i += 128) *(uint4*)(smraw + H_MEM + i * 16) = *(const uint4*)(mem0 + (i & 7) * 576 + (i >> 4) * 8);
    if (t < 8) *(uint4*)(smraw + H_VB + 10240 + t * 16) = make_uint4(0, 0, 0, 0);
    fence_async();
    asm volatile("barrier.cluster.arrive.release.aligned; barrier.cluster.wait.acquire.aligned;" ::: "memory");
    if (t == 96) { x_load(sb, 0, 0, LF, 0, (epoch + 1) * 8); x_load(sb, 1, 0, LS, 0, (epoch + 1) * 8); x_load(sb, 2, 0, LF, 1, (epoch + 1) * 8); }
    __syncwarp();
    uint32_t ps = 1, pp = 1;
    uint32_t aph = 0;
    uint32_t ring = (epoch * (NSTEP - 1)) & 3;
    for (int s = 0; s < NSTEP; s++) {
      const bool u0 = act(0, s) && act(0, s + 1), u1 = act(1, s) && act(1, s + 1);
      const bool mine = j < 2 && act(j, s);
      if (mine) {
        float sc[20];
        mbar_wait(sb + H_BAR + B_QK, aph);
        TR(8);
        fence_async();
        wg_fence();
        {
          const uint64_t qd = mkdesc(sb + H_QB, 640, 128), kd = mkdesc(sb + H_KB, 640, 128);
#pragma unroll
          for (int kk = 0; kk < 8; kk++) { if (kk == 0) ss40tt<0>(sc, qd, kd); else ss40tt<1>(sc, qd + kk * 80, kd + kk * 80); }
        }
        wg_commit();
        mbar_wait(sb + H_BAR + B_V, aph);
        if (t == 0) { mbar_expect(sb + H_BAR + B_QK, 10240); mbar_expect(sb + H_BAR + B_V, 10240); }
        aph ^= 1;
        fence_async();
        wg_wait<0>(); pin<20>(sc);
        TR(7);
        int tl = t; OPAQUE(tl);
        const float cs = 0.08838834764831845f * 1.4426950408889634f;
        const int r0 = (tl < 64) ? ((tl & 31) >> 2) * 2 + (tl >> 5) - 4 * (tl & 3) : 31, r1 = r0 + 16;
        float m0 = fmaxf(sc[16], sc[17]), m1 = fmaxf(sc[18], sc[19]);
#pragma unroll
        for (int i = 0; i < 4; i++) {
          const int c = 16 * (i & 1) + (i >> 1);
          if (c > r0) sc[4 * i] = -INFINITY;
          if (c + 2 > r0) sc[4 * i + 1] = -INFINITY;
          if (i & 1) { if (c > r1) sc[4 * i + 2] = -INFINITY; if (c + 2 > r1) sc[4 * i + 3] = -INFINITY; }
          m0 = fmaxf(m0, fmaxf(sc[4 * i], sc[4 * i + 1])); m1 = fmaxf(m1, fmaxf(sc[4 * i + 2], sc[4 * i + 3]));
        }
        m0 = fmaxf(m0, __shfl_xor_sync(~0u, m0, 1)); m1 = fmaxf(m1, __shfl_xor_sync(~0u, m1, 1));
        m0 = fmaxf(m0, __shfl_xor_sync(~0u, m0, 2)); m1 = fmaxf(m1, __shfl_xor_sync(~0u, m1, 2));
        m0 *= cs; m1 *= cs;
        float s0 = 0.f, s1 = 0.f;
#pragma unroll
        for (int i = 0; i < 5; i++) {
          sc[4 * i] = ex2(fmaf(sc[4 * i], cs, -m0)); sc[4 * i + 1] = ex2(fmaf(sc[4 * i + 1], cs, -m0));
          sc[4 * i + 2] = ex2(fmaf(sc[4 * i + 2], cs, -m1)); sc[4 * i + 3] = ex2(fmaf(sc[4 * i + 3], cs, -m1));
          s0 += sc[4 * i] + sc[4 * i + 1]; s1 += sc[4 * i + 2] + sc[4 * i + 3];
        }
        uint32_t pa[12];
#pragma unroll
        for (int i = 0; i < 5; i++) { pa[2 * i] = pk(sc[4 * i], sc[4 * i + 1]); pa[2 * i + 1] = pk(sc[4 * i + 2], sc[4 * i + 3]); }
        asm volatile("ld.shared.v2.b32 {%0,%1}, [%2];" : "=r"(pa[10]), "=r"(pa[11]) : "r"(sb + H_VB + 10240));
        TR(4);
        const uint64_t vd = mkdesc(sb + H_VB, 128, 640);
        float o[2][32];
        wg_fence();
        rs64<0>(o[0], pa, vd); rs64<0>(o[1], pa, vd + 320);
        rs64<1>(o[0], pa + 4, vd + 16); rs64<1>(o[1], pa + 4, vd + 320 + 16);
        rs64<1>(o[0], pa + 8, vd + 32); wg_commit();
        rs64<1>(o[1], pa + 8, vd + 320 + 32); wg_commit();
        s0 += __shfl_xor_sync(~0u, s0, 1); s1 += __shfl_xor_sync(~0u, s1, 1);
        s0 += __shfl_xor_sync(~0u, s0, 2); s1 += __shfl_xor_sync(~0u, s1, 2);
        s0 = rcp(s0); s1 = rcp(s1);
        if ((tl >> 5) == 2) {
          const uint32_t omo = (sb & 0xFFFFFF) + H_MEM + j * 4096 + (tl & 3) * 256 + ((tl >> 2) & 7) * 16;
          const uint32_t omb = (sb & 0xFFFFFF) + H_BAR + B_OM;
          const uint32_t rr = (uint32_t)(1 - j) << 24, rl = (uint32_t)j << 24;
          const bool um = (j == 0 ? u0 : u1);
          uint32_t x[16];
#pragma unroll
          for (int hf = 0; hf < 2; hf++) {
            if (hf == 0) wg_wait<1>(); else wg_wait<0>();
            pin<32>(o[hf]);
#pragma unroll
            for (int i = 0; i < 8; i++) x[hf * 8 + i] = pk(o[hf][4 * i] * s0, o[hf][4 * i + 1] * s0);
            if (um) {
#pragma unroll
              for (int jg = 2 * hf; jg < 2 * hf + 2; jg++) {
                st_async4(omo + jg * 1024 + rr, x[4 * jg], x[4 * jg + 1], x[4 * jg + 2], x[4 * jg + 3], omb + rr);
                st_async4(omo + jg * 1024 + (2u << 24), x[4 * jg], x[4 * jg + 1], x[4 * jg + 2], x[4 * jg + 3], omb + (2u << 24));
              }
            }
          }
          if ((tl & 31) == 0) mbar_arrive(sb + H_BAR + B_W2);
#pragma unroll
          for (int jg = 0; jg < 4; jg++) sts4(omo + jg * 1024 + rl, x[4 * jg], x[4 * jg + 1], x[4 * jg + 2], x[4 * jg + 3]);
          __syncwarp();
          if ((tl & 31) == 0 && s < NSTEP - 1) mbar_arrive(sb + H_BAR + B_OM);
        } else {
          wg_wait<0>();
          pin<32>(o[0]); pin<32>(o[1]);
          if ((tl & 31) == 0) mbar_arrive(sb + H_BAR + B_W2);
          TR(9);
          if (tl < 64) {
            const uint32_t os = sb + H_OS + (tl >> 5) * 4096 + (tl & 31) * 16;
#pragma unroll
            for (int kk = 0; kk < 8; kk++) {
              const float* oo = &o[kk >> 2][(kk & 3) * 8];
              sts4(os + kk * 512, pk(oo[0] * s0, oo[1] * s0), pk(oo[2] * s1, oo[3] * s1), pk(oo[4] * s0, oo[5] * s0), pk(oo[6] * s1, oo[7] * s1));
            }
            fence_async();
          }
        }
      } else {
        if ((t & 31) == 0) mbar_arrive(sb + H_BAR + B_W2);
        if (j < 2 && t == 64 && s < NSTEP - 1) mbar_arrive(sb + H_BAR + B_OM);
      }
      if (s < NSTEP - 1) {
        int tl = t; OPAQUE(tl);
        const uint32_t wb = sb + H_WO + (tl >> 5) * 6 * 2048 + (tl & 31) * 16;
        constexpr int NB = 3;
        uint32_t bq[NB][12];
#pragma unroll
        for (int u = 0; u < NB; u++)
#pragma unroll
          for (int tt = 0; tt < 3; tt++) ldsm4t(&bq[u][tt * 4], wb + tt * 2048 + u * 512);
        uint4* pacc = &g_acc[0][0] + (uint32_t)(ring * 1536 + j * 128 + tl);
        const uint32_t oa = sb + H_MEM + ((tl >> 3) & 1) * 4096 + ((tl >> 4) & 1) * 256 + (tl & 7) * 16;
        mbar_wait(sb + H_BAR + B_OM, s & 1);
        TR(10);
        uint32_t A[8][4];
#pragma unroll
        for (int kk = 0; kk < 8; kk++) ldsm4(A[kk], oa + kk * 512);
#pragma unroll
        for (int a = 0; a < 2; a++) {
          float d[3][4], e[3][4];
#pragma unroll
          for (int tt = 0; tt < 3; tt++) { d[tt][0] = d[tt][1] = d[tt][2] = d[tt][3] = 0.f; e[tt][0] = e[tt][1] = e[tt][2] = e[tt][3] = 0.f; }
#pragma unroll
          for (int jg = 0; jg < 4; jg++) {
            const int u = a * 4 + jg, un = u + NB;
            uint32_t* b = bq[u % NB];
#pragma unroll
            for (int tt = 0; tt < 3; tt++) HMMA(d[tt], A[2 * jg][0], A[2 * jg][1], A[2 * jg][2], A[2 * jg][3], b[tt * 4], b[tt * 4 + 1]);
#pragma unroll
            for (int tt = 0; tt < 3; tt++) {
              HMMA(e[tt], A[2 * jg + 1][0], A[2 * jg + 1][1], A[2 * jg + 1][2], A[2 * jg + 1][3], b[tt * 4 + 2], b[tt * 4 + 3]);
              if (un < 8) ldsm4t(&b[tt * 4], wb + ((un >> 2) * 3 + tt) * 2048 + (un & 3) * 512);
            }
          }
#pragma unroll
          for (int tt = 0; tt < 3; tt++) { d[tt][0] += e[tt][0]; d[tt][1] += e[tt][1]; d[tt][2] += e[tt][2]; d[tt][3] += e[tt][3]; }
          if (u0) red4(pacc + a * 768, pk(d[0][0], d[0][1]), pk(d[1][0], d[1][1]), pk(d[2][0], d[2][1]));
          if (u1) red4(pacc + a * 768 + 384, pk(d[0][2], d[0][3]), pk(d[1][2], d[1][3]), pk(d[2][2], d[2][3]));
        }
        if ((tl & 31) == 0) mbar_arrive(sb + H_BAR + B_W3);
        TR(11);
        const uint32_t c0 = clock();
        if (t == 0 && s < NSTEP - 2) {
          const uint32_t n0 = act(0, s + 1) && act(0, s + 2), n1 = act(1, s + 1) && act(1, s + 2);
          mbar_expect(sb + H_BAR + B_OM, ((j == 0 ? 0 : n0) + (j == 1 ? 0 : n1)) * 2048);
        }
        const uint32_t rot = blockIdx.x, wr_ = ((tl >> 5) + (rot >> 3)) & 3, lf = (rot >> 2) & 1;
        const uint32_t la = u0 && u1 ? lf : (u0 ? 0 : 1), lb = u0 && u1 ? 1 - lf : la;
        const uint4* pa0 = &g_acc[0][0] + (uint32_t)(ring * 1536 + wr_ * 32 + (tl & 31));
        const uint32_t mo = sb + H_MEM + wr_ * 768 + (tl & 31) * 4;
        uint32_t go[6], so[6];
#pragma unroll
        for (int i = 0; i < 3; i++) {
          const uint32_t jj = (j + i) >= 3 ? j + i - 3 : j + i;
          go[2 * i] = la * 384 + jj * 128; go[2 * i + 1] = lb * 384 + jj * 128;
          so[2 * i] = mo + la * 128 + jj * 3072; so[2 * i + 1] = mo + lb * 128 + jj * 3072;
        }
        mbar_wait(sb + H_BAR + B_W3, s & 1);
        uint4 v[2][6];
        while ((uint32_t)clock() - c0 < PD) {}
#pragma unroll
        for (int i = 0; i < 6; i++) v[0][i] = ld_rlx(pa0 + go[i]);
        while ((uint32_t)clock() - c0 < PD2) {}
#pragma unroll
        for (int i = 0; i < 6; i++) v[1][i] = ld_rlx(pa0 + go[i] + 768);
        if (mine && tl < 64 && (tl & 31) == 0)
          bulk_s2g(&g_O[j][(s - j * LAG) % ORING][tl >> 5][8 * h][0], sb + H_OS + (tl >> 5) * 4096, 4096);
#pragma unroll
        for (int a = 0; a < 2; a++) {
          uint32_t it = 0;
          while (true) {
            bool ok = true;
#pragma unroll
            for (int i = 0; i < 6; i++) ok = ok && v[a][i].w == 0x4200u;
            if (__all_sync(~0u, ok)) break;
            if (++it > SPIN_MAX) __trap();
#pragma unroll
            for (int i = 0; i < 6; i++) if (v[a][i].w != 0x4200u) v[a][i] = ld_rlx(pa0 + go[i] + a * 768);
          }
          if (a == 0) { TR(12); }
#pragma unroll
          for (int i = 0; i < 6; i++) { sts1(so[i] + a * 9216, v[a][i].x); sts1(so[i] + a * 9216 + 256, v[a][i].y); sts1(so[i] + a * 9216 + 512, v[a][i].z); }
          __syncwarp();
          if ((tl & 31) == 0) mbar_arrive(sb + H_BAR + B_MEM + a * 8);
        }
        if (tl >= 64 && tl < 80) st_rlx(&g_acc[0][0] + (uint32_t)(((ring + 3) & 3) * 1536 + blockIdx.x * 16 + tl - 64), make_uint4(0, 0, 0, 0));
        ring = (ring + 1) & 3;
        if (t == 96 && s < NSTEP - 2) x_load(sb, ps, pp, LF, s + 2, (epoch + 1) * 8);
        ps += 2; if (ps >= 3) { ps -= 3; pp ^= 1; }
      } else {
        __syncwarp();
        if (mine && t < 64 && (t & 31) == 0)
          bulk_s2g(&g_O[j][(s - j * LAG) % ORING][t >> 5][8 * h][0], sb + H_OS + (t >> 5) * 4096, 4096);
      }
      if (mine && t < 64 && (t & 31) == 0) {
        asm volatile("cp.async.bulk.wait_group 0; fence.proxy.async.global;" ::: "memory");
        asm volatile("st.release.gpu.global.u32 [%0], %1;" :: "l"(&g_fO[j][s - j * LAG][t >> 5][h]), "r"(epoch + 1) : "memory");
      }
      __syncwarp();
      TR(14);
    }
    asm volatile("barrier.cluster.arrive.release.aligned; barrier.cluster.wait.acquire.aligned;" ::: "memory");
  }
}

constexpr int G_W = 21, G_AQ = 11, G_AO = 4;
constexpr uint32_t G_SMEM = 232448;

template<int N, int NK, class F> __device__ __forceinline__ void gemm_rs(float* acc, uint32_t* a, uint32_t baddr, F&& reload) {
  constexpr int R = NK - 24;
  const uint64_t bd = mkdesc(baddr, N * 16, 128);
  auto step = [&](int kk, int slot, bool first) {
    if (N == 192) { if (first) rs192t<0>(acc, &a[slot * 4], bd); else rs192t<1>(acc, &a[slot * 4], bd + kk * (N * 2)); }
    if (N == 168) { if (first) rs168t<0>(acc, &a[slot * 4], bd); else rs168t<1>(acc, &a[slot * 4], bd + kk * (N * 2)); }
    if (N == 144) { if (first) rs144t<0>(acc, &a[slot * 4], bd); else rs144t<1>(acc, &a[slot * 4], bd + kk * (N * 2)); }
  };
  wg_fence();
#pragma unroll
  for (int kk = 0; kk < R; kk++) step(kk, kk, kk == 0);
  wg_commit();
  step(R, R, false);
  wg_commit();
  wg_wait<1>();
#pragma unroll
  for (int i = 0; i < R; i++) reload(&a[i * 4], 24 + i);
  wg_fence();
#pragma unroll
  for (int kk = R + 1; kk < 24; kk++) step(kk, kk, false);
  wg_commit();
  wg_fence();
#pragma unroll
  for (int kk = 24; kk < NK; kk++) step(kk, kk - 24, false);
  wg_commit();
  wg_wait<0>();
  pin<N / 2>(acc);
}

__device__ __forceinline__ float warp_sum(float v) {
#pragma unroll
  for (int o = 16; o; o >>= 1) v += __shfl_xor_sync(~0u, v, o);
  return v;
}

__device__ __forceinline__ void role_W(uint8_t* smraw, uint32_t sb, int c, uint32_t epoch, const bf16* __restrict__ x, const bf16* __restrict__ Wo, bf16* __restrict__ out) {
  const int tid = threadIdx.x, lane = tid & 31, w = __shfl_sync(~0u, (tid >> 5) & 3, 0), wg = __shfl_sync(~0u, tid >> 7, 0);
  const int ks = c / 3, ns = c % 3, k0 = ks * 37;
  for (int i = tid; i < 592 * 24; i += 256) {
    const int k = i / 24, nb = i % 24;
    const uint32_t dst = sb + (k >> 3) * 3072 + nb * 128 + (k & 7) * 16;
    if (k0 * 16 + k < 4096) cp16(dst, Wo + (size_t)(k0 * 16 + k) * 576 + ns * 192 + nb * 8); else sts4(dst, 0, 0, 0, 0);
  }
  asm volatile("cp.async.commit_group;" ::: "memory");
  for (int u = c * 8 + (tid >> 5); u < NSEG * 16; u += G_W * 8) {
    const int seg = u >> 4, rb = (u >> 3) & 1, g = u & 7;
    const uint32_t* p0 = (const uint32_t*)(x + (size_t)(seg * 32 + 2 * g + rb) * 576) + (lane >> 2) * 8 + (lane & 3);
    uint32_t v[5][4];
    float s0 = 0.f, s1 = 0.f;
#pragma unroll
    for (int i = 0; i < 5; i++) {
      const bool on = i < 4 || lane < 16;
      v[i][0] = on ? __ldg(p0 + i * 64) : 0; v[i][2] = on ? __ldg(p0 + i * 64 + 4) : 0;
      v[i][1] = on ? __ldg(p0 + i * 64 + 16 * 288) : 0; v[i][3] = on ? __ldg(p0 + i * 64 + 16 * 288 + 4) : 0;
    }
#pragma unroll
    for (int i = 0; i < 5; i++) { s0 += blo(v[i][0]) + bhi(v[i][0]) + blo(v[i][2]) + bhi(v[i][2]); s1 += blo(v[i][1]) + bhi(v[i][1]) + blo(v[i][3]) + bhi(v[i][3]); }
    const float m0 = warp_sum(s0) * (1.f / 576), m1 = warp_sum(s1) * (1.f / 576);
    float q0 = 0.f, q1 = 0.f;
#pragma unroll
    for (int i = 0; i < 5; i++) if (i < 4 || lane < 16) {
      float a;
      a = blo(v[i][0]) - m0; q0 += a * a; a = bhi(v[i][0]) - m0; q0 += a * a; a = blo(v[i][2]) - m0; q0 += a * a; a = bhi(v[i][2]) - m0; q0 += a * a;
      a = blo(v[i][1]) - m1; q1 += a * a; a = bhi(v[i][1]) - m1; q1 += a * a; a = blo(v[i][3]) - m1; q1 += a * a; a = bhi(v[i][3]) - m1; q1 += a * a;
    }
    const float r0 = rsqrtf(warp_sum(q0) * (1.f / 576) + 1e-5f), r1 = rsqrtf(warp_sum(q1) * (1.f / 576) + 1e-5f);
    const int o = (rb * 36 + (lane >> 2)) * 32 + g * 4 + (lane & 3);
#pragma unroll
    for (int i = 0; i < 5; i++) if (i < 4 || lane < 16) {
      g_xr[0][seg][o + i * 256] = make_uint4(v[i][0], v[i][1], v[i][2], v[i][3]);
      g_xnA[0][seg][o + i * 256] = make_uint4(pk((blo(v[i][0]) - m0) * r0, (bhi(v[i][0]) - m0) * r0), pk((blo(v[i][1]) - m1) * r1, (bhi(v[i][1]) - m1) * r1),
                                              pk((blo(v[i][2]) - m0) * r0, (bhi(v[i][2]) - m0) * r0), pk((blo(v[i][3]) - m1) * r1, (bhi(v[i][3]) - m1) * r1));
    }
    flag_add(&g_fXA[0][seg][rb][0]);
  }
  asm volatile("cp.async.wait_group 0;" ::: "memory");
  fence_async();
  __syncthreads();
  const int L = w >> 1, rb = w & 1;
  float* sst = (float*)(smraw + 227328) + wg * 16;
  for (int s = wg; s < NSTEP; s += 2) {
    const int seg = s - L * LAG;
    const bool on = (uint32_t)seg < (uint32_t)NSEG;
    float acc[96];
    uint32_t a[96];
    const uint4* pa = &g_O[L][(on ? seg : 0) % ORING][rb][0][lane];
    if (on) {
      const int hh = min((k0 >> 3) + min(lane, 5), min((k0 + 36) >> 3, 31));
      uint32_t it = 0;
      while (!__all_sync(~0u, ld_acq(&g_fO[L][seg][rb][hh]) == epoch + 1)) { if (++it > SPIN_MAX) __trap(); }
    }
    GT(s, 0);
#pragma unroll
    for (int i = 0; i < 24; i++) ld_rlx(&a[i * 4], pa + (k0 + i) * 32);
    gemm_rs<192, 37>(acc, a, sb, [&](uint32_t* r, int kk) { ld_rlx(r, pa + min(k0 + kk, 255) * 32); });
    GT(s, 1);
    if (on) {
      uint4* pp = &g_P[L][seg % PRING][ks][rb][ns * 12][lane];
#pragma unroll
      for (int i = 0; i < 12; i++)
        pp[i * 32] = make_uint4(pk(acc[8 * i], acc[8 * i + 1]), pk(acc[8 * i + 2], acc[8 * i + 3]), pk(acc[8 * i + 4], acc[8 * i + 5]), pk(acc[8 * i + 6], acc[8 * i + 7]));
      flag_add(&g_fP[L][seg][rb][0]);
    }
    if (c < 16 && on) {
      const int ub = c >> 3, g = c & 7;
      flag_wait(&g_fP[L][seg][ub][0], (epoch + 1) * G_W);
      GT(s, 2);
      const int o = (ub * 36 + rb * 18 + (lane >> 2)) * 32 + g * 4 + (lane & 3);
      const uint4* pp = &g_P[L][seg % PRING][0][0][0][0] + o;
      uint32_t v[3][8][4];
#pragma unroll
      for (int i = 0; i < 3; i++) if (i < 2 || lane < 8) {
#pragma unroll
        for (int k = 0; k < 7; k++) ld_rlx(v[i][k], pp + k * 2304 + i * 256);
        ld_rlx(v[i][7], &g_xr[1 + 2 * L][seg][o + i * 256]);
      }
      uint32_t y[3][4];
#pragma unroll
      for (int i = 0; i < 3; i++)
#pragma unroll
        for (int r = 0; r < 4; r++) {
          float lo = 0.f, hi = 0.f;
          if (i < 2 || lane < 8) {
#pragma unroll
            for (int k = 0; k < 8; k++) { lo += blo(v[i][k][r]); hi += bhi(v[i][k][r]); }
          }
          y[i][r] = pk(lo, hi);
        }
      if (L == 0) {
        float s0 = 0.f, s1 = 0.f;
#pragma unroll
        for (int i = 0; i < 3; i++) { s0 += blo(y[i][0]) + bhi(y[i][0]) + blo(y[i][2]) + bhi(y[i][2]); s1 += blo(y[i][1]) + bhi(y[i][1]) + blo(y[i][3]) + bhi(y[i][3]); }
        float m0 = warp_sum(s0) * (1.f / 288), m1 = warp_sum(s1) * (1.f / 288);
        float q0 = 0.f, q1 = 0.f;
#pragma unroll
        for (int i = 0; i < 3; i++) if (i < 2 || lane < 8) {
          float a_;
          a_ = blo(y[i][0]) - m0; q0 += a_ * a_; a_ = bhi(y[i][0]) - m0; q0 += a_ * a_; a_ = blo(y[i][2]) - m0; q0 += a_ * a_; a_ = bhi(y[i][2]) - m0; q0 += a_ * a_;
          a_ = blo(y[i][1]) - m1; q1 += a_ * a_; a_ = bhi(y[i][1]) - m1; q1 += a_ * a_; a_ = blo(y[i][3]) - m1; q1 += a_ * a_; a_ = bhi(y[i][3]) - m1; q1 += a_ * a_;
        }
        q0 = warp_sum(q0); q1 = warp_sum(q1);
        float* st = sst + ((s >> 1) & 1) * 8;
        if (lane == 0) *(float4*)(st + rb * 4) = make_float4(m0, q0, m1, q1);
        asm volatile("bar.sync %0, 64;" :: "r"(2 + wg) : "memory");
        const float4 ot = *(const float4*)(st + (rb ^ 1) * 4);
        const float d0 = m0 - ot.x, d1 = m1 - ot.z;
        m0 = 0.5f * (m0 + ot.x); m1 = 0.5f * (m1 + ot.z);
        const float r0 = rsqrtf((q0 + ot.y + d0 * d0 * 144.f) * (1.f / 576) + 1e-5f), r1 = rsqrtf((q1 + ot.w + d1 * d1 * 144.f) * (1.f / 576) + 1e-5f);
#pragma unroll
        for (int i = 0; i < 3; i++) if (i < 2 || lane < 8) {
          g_xnA[1][seg][o + i * 256] = make_uint4(pk((blo(y[i][0]) - m0) * r0, (bhi(y[i][0]) - m0) * r0), pk((blo(y[i][1]) - m1) * r1, (bhi(y[i][1]) - m1) * r1),
                                                  pk((blo(y[i][2]) - m0) * r0, (bhi(y[i][2]) - m0) * r0), pk((blo(y[i][3]) - m1) * r1, (bhi(y[i][3]) - m1) * r1));
          g_xr[2][seg][o + i * 256] = make_uint4(y[i][0], y[i][1], y[i][2], y[i][3]);
        }
        flag_add(&g_fXA[1][seg][ub][0]);
      } else {
        uint32_t* po = (uint32_t*)(out + (size_t)(seg * 32 + 2 * g + ub) * 576) + (rb * 18 + (lane >> 2)) * 8 + (lane & 3);
#pragma unroll
        for (int i = 0; i < 3; i++) if (i < 2 || lane < 8) {
          po[i * 64] = y[i][0]; po[i * 64 + 4] = y[i][2]; po[i * 64 + 16 * 288] = y[i][1]; po[i * 64 + 16 * 288 + 4] = y[i][3];
        }
        if (c == 0 && s == NSTEP - 1 && rb == 0 && lane == 0) g_epoch = epoch + 1;
      }
      GT(s, 3);
    }
  }
}

constexpr uint32_t AQ_KV = 193536, AQ_Q = AQ_KV + 4 * 24 * 304;
__device__ __forceinline__ void role_AQ(uint8_t* smraw, uint32_t sb, int c, uint32_t epoch, const bf16* __restrict__ wqkv) {
  const int tid = threadIdx.x, lane = tid & 31, w = __shfl_sync(~0u, (tid >> 5) & 3, 0), wg = __shfl_sync(~0u, tid >> 7, 0);
  const int ncol = min(54, 576 - 54 * c);
  for (int i = tid; i < 576 * 84; i += 256) {
    const int k = i / 84, r = i % 84, part = r / 28, cw = r % 28;
    const uint32_t dst = sb + (k >> 3) * 2688 + (part * 7 + (cw >> 2)) * 128 + (k & 7) * 16 + (cw & 3) * 4;
    if (2 * cw < ncol) cp4(dst, wqkv + (size_t)k * 1728 + part * 576 + 54 * c + 2 * cw); else sts1(dst, 0);
  }
  for (int i = tid; i < (4 * 24 * 304 + 4 * 16 * 144) / 16; i += 256) sts4(sb + AQ_KV + i * 16, 0, 0, 0, 0);
  cp_wait_all();
  fence_async();
  __syncthreads();
  const int st = w >> 1, rb = w & 1, g = lane >> 2, q = lane & 3;
  const uint32_t kvb = sb + AQ_KV + w * 24 * 304, qb = sb + AQ_Q + w * 16 * 144;
  if (wg == 1) asm volatile("bar.arrive 2, 256;" ::: "memory");
  for (int n = wg; n < NSEG + LEAD; n += 2) {
    const int seg = n - st * LEAD;
    const bool on = (uint32_t)seg < (uint32_t)NSEG;
    float acc[84];
    uint32_t a[96];
    const uint4* pa = &g_xnA[st][on ? seg : 0][rb * 36 * 32 + lane];
    if (on) flag_wait(&g_fXA[st][seg][rb][0], (epoch + 1) * (st ? 16 : 8));
    GT(n, 0);
#pragma unroll
    for (int i = 0; i < 24; i++) ld_rlx(&a[i * 4], pa + i * 32);
    asm volatile("bar.sync %0, 256;" :: "r"(2 + wg) : "memory");
    gemm_rs<168, 36>(acc, a, sb, [&](uint32_t* r, int kk) { ld_rlx(r, pa + kk * 32); });
    GT(n, 1);
    uint32_t ow[3][3][2];
    if (on) {
      const uint32_t pos0 = (2 * n) % 3, pos1 = (2 * n + 1) % 3, pos2 = (2 * n + 2) % 3;
#pragma unroll
      for (int jn = 0; jn < 21; jn++) {
        const int part = jn / 7, cc = 8 * (jn % 7) + 2 * q;
        const uint32_t co = 2 * cc + 12 * ((cc >= 18) + (cc >= 36));
        const uint32_t lo = part == 0 ? qb + g * 144 + co : kvb + (pos1 * 8 + g) * 304 + (part - 1) * 144 + co;
        const uint32_t hi = part == 0 ? lo + 8 * 144 : kvb + (pos2 * 8 + g) * 304 + (part - 1) * 144 + co;
        if (cc < 54) { sts1(lo, pk(acc[4 * jn], acc[4 * jn + 1])); sts1(hi, pk(acc[4 * jn + 2], acc[4 * jn + 3])); }
      }
      __syncwarp();
      const uint32_t ka = kvb + (lane & 7) * 304 + min(lane >> 3, 2) * 16;
      const float cs = 0.23570226039551584f * 1.4426950408889634f;
#pragma unroll
      for (int lh = 0; lh < 3; lh++) {
        uint32_t qa[4], qc[2], kf[3][4], vf[3][4];
        ldsm4(qa, qb + (lane & 15) * 144 + (lane >> 4) * 16 + lh * 48);
        ldsm2(qc, qb + (lane & 15) * 144 + 32 + lh * 48);
        ldsm4(kf[0], ka + pos0 * 2432 + lh * 48); ldsm4(kf[1], ka + pos1 * 2432 + lh * 48); ldsm4(kf[2], ka + pos2 * 2432 + lh * 48);
        ldsm4t(vf[0], ka + pos0 * 2432 + 144 + lh * 48); ldsm4t(vf[1], ka + pos1 * 2432 + 144 + lh * 48); ldsm4t(vf[2], ka + pos2 * 2432 + 144 + lh * 48);
        float sc[3][4];
#pragma unroll
        for (int b = 0; b < 3; b++) {
          sc[b][0] = sc[b][1] = sc[b][2] = sc[b][3] = 0.f;
          HMMA(sc[b], qa[0], qa[1], qa[2], qa[3], kf[b][0], kf[b][1]);
          HMMA8(sc[b], qc[0], qc[1], kf[b][2]);
        }
        const bool e0 = 2 * q <= g, e1 = 2 * q + 1 <= g;
        float a0 = e0 ? sc[1][0] : (seg > 0 ? sc[0][0] : -INFINITY), a1 = e1 ? sc[1][1] : (seg > 0 ? sc[0][1] : -INFINITY);
        float b0 = e0 ? sc[2][2] : sc[1][2], b1 = e1 ? sc[2][3] : sc[1][3];
        float m0 = fmaxf(a0, a1), m1 = fmaxf(b0, b1);
        m0 = fmaxf(m0, __shfl_xor_sync(~0u, m0, 1)); m1 = fmaxf(m1, __shfl_xor_sync(~0u, m1, 1));
        m0 = fmaxf(m0, __shfl_xor_sync(~0u, m0, 2)); m1 = fmaxf(m1, __shfl_xor_sync(~0u, m1, 2));
        a0 = ex2((a0 - m0) * cs); a1 = ex2((a1 - m0) * cs); b0 = ex2((b0 - m1) * cs); b1 = ex2((b1 - m1) * cs);
        float s0 = a0 + a1, s1 = b0 + b1;
        s0 += __shfl_xor_sync(~0u, s0, 1); s1 += __shfl_xor_sync(~0u, s1, 1);
        s0 += __shfl_xor_sync(~0u, s0, 2); s1 += __shfl_xor_sync(~0u, s1, 2);
        s0 = rcp(s0); s1 = rcp(s1);
        a0 *= s0; a1 *= s0; b0 *= s1; b1 *= s1;
        const uint32_t p00 = pk(e0 ? 0.f : a0, e1 ? 0.f : a1), p01 = pk(e0 ? a0 : 0.f, e1 ? a1 : 0.f);
        const uint32_t p11 = pk(e0 ? 0.f : b0, e1 ? 0.f : b1), p12 = pk(e0 ? b0 : 0.f, e1 ? b1 : 0.f);
#pragma unroll
        for (int cb = 0; cb < 3; cb++) {
          float o[4] = {0.f, 0.f, 0.f, 0.f};
          HMMA(o, p00, 0u, p01, p11, vf[0][cb], vf[1][cb]);
          HMMA8(o, 0u, p12, vf[2][cb]);
          ow[lh][cb][0] = pk(o[0], o[1]); ow[lh][cb][1] = pk(o[2], o[3]);
        }
      }
    }
    asm volatile("bar.arrive %0, 256;" :: "r"(3 - wg) : "memory");
    if (on) {
      uint2* po = (uint2*)&g_oA[st][seg][rb * 36 * 32 + g * 4];
#pragma unroll
      for (int lh = 0; lh < 3; lh++)
#pragma unroll
        for (int cb = 0; cb < 3; cb++) {
          const int col = 54 * c + 18 * lh + 8 * cb + 2 * q;
          if ((cb < 2 || q == 0) && col < 576) po[(col >> 4) * 64 + (col & 6) + ((col >> 3) & 1)] = make_uint2(ow[lh][cb][0], ow[lh][cb][1]);
        }
      flag_add(&g_fOA[st][seg][rb][0]);
    }
    GT(n, 2);
  }
  if (wg == ((NSEG + LEAD) & 1)) asm volatile("bar.sync %0, 256;" :: "r"(2 + wg) : "memory");
}

__device__ __forceinline__ void role_AO(uint8_t* smraw, uint32_t sb, int c, uint32_t epoch, const bf16* __restrict__ wo) {
  const int tid = threadIdx.x, lane = tid & 31, w = __shfl_sync(~0u, (tid >> 5) & 3, 0), wg = __shfl_sync(~0u, tid >> 7, 0);
  for (int i = tid; i < 576 * 18; i += 256) {
    const int k = i / 18, nb = i % 18;
    cp16(sb + (k >> 3) * 2304 + nb * 128 + (k & 7) * 16, wo + (size_t)k * 576 + c * 144 + nb * 8);
  }
  cp_wait_all();
  fence_async();
  __syncthreads();
  const int st = w >> 1, rb = w & 1, g = lane >> 2, q = lane & 3;
  const uint32_t tag = (epoch + 1) & 1;
  for (int n = wg; n < NSEG + LEAD; n += 2) {
    const int seg = n - st * LEAD;
    const bool on = (uint32_t)seg < (uint32_t)NSEG;
    float acc[72];
    uint32_t a[96], res[9][4];
    const uint4* pa = &g_oA[st][on ? seg : 0][rb * 36 * 32 + lane];
    if (on) flag_wait(&g_fOA[st][seg][rb][0], (epoch + 1) * G_AQ);
    GT(n, 0);
#pragma unroll
    for (int i = 0; i < 24; i++) ld_rlx(&a[i * 4], pa + i * 32);
    const int o = (rb * 36 + c * 9) * 32 + lane;
#pragma unroll
    for (int i = 0; i < 9; i++) ld_rlx(res[i], &g_xr[2 * st][on ? seg : 0][o + i * 32]);
    gemm_rs<144, 36>(acc, a, sb, [&](uint32_t* r, int kk) { ld_rlx(r, pa + kk * 32); });
    GT(n, 1);
    if (on) {
      float s0 = 0.f, s1 = 0.f;
#pragma unroll
      for (int i = 0; i < 36; i++) {
        const uint32_t y = pk(acc[2 * i] + blo(res[i >> 2][i & 3]), acc[2 * i + 1] + bhi(res[i >> 2][i & 3]));
        res[i >> 2][i & 3] = y;
        acc[2 * i] = blo(y); acc[2 * i + 1] = bhi(y);
        if (i & 1) s1 += acc[2 * i] + acc[2 * i + 1]; else s0 += acc[2 * i] + acc[2 * i + 1];
      }
      s0 += __shfl_xor_sync(~0u, s0, 1); s1 += __shfl_xor_sync(~0u, s1, 1);
      s0 += __shfl_xor_sync(~0u, s0, 2); s1 += __shfl_xor_sync(~0u, s1, 2);
      float m0 = s0 * (1.f / 144), m1 = s1 * (1.f / 144), q0 = 0.f, q1 = 0.f;
#pragma unroll
      for (int i = 0; i < 36; i++) {
        const float mm = (i & 1) ? m1 : m0, d0 = acc[2 * i] - mm, d1 = acc[2 * i + 1] - mm;
        if (i & 1) q1 += d0 * d0 + d1 * d1; else q0 += d0 * d0 + d1 * d1;
      }
      q0 += __shfl_xor_sync(~0u, q0, 1); q1 += __shfl_xor_sync(~0u, q1, 1);
      q0 += __shfl_xor_sync(~0u, q0, 2); q1 += __shfl_xor_sync(~0u, q1, 2);
      if (q == 0) st_rlx(&g_stat[st][seg][rb][c * 8 + g], make_uint4(__float_as_uint(m0), (__float_as_uint(q0) & ~1u) | tag, __float_as_uint(m1), __float_as_uint(q1)));
#pragma unroll
      for (int i = 0; i < 9; i++) g_xr[1 + 2 * st][seg][o + i * 32] = make_uint4(res[i][0], res[i][1], res[i][2], res[i][3]);
      uint4 sv;
      {
        uint32_t it = 0;
        do { sv = ld_rlx(&g_stat[st][seg][rb][q * 8 + g]); if (++it > SPIN_MAX) __trap(); } while (!__all_sync(~0u, (sv.y & 1) == tag));
      }
      m0 = __uint_as_float(sv.x); m1 = __uint_as_float(sv.z);
      float t0 = m0 + __shfl_xor_sync(~0u, m0, 1), t1 = m1 + __shfl_xor_sync(~0u, m1, 1);
      t0 += __shfl_xor_sync(~0u, t0, 2); t1 += __shfl_xor_sync(~0u, t1, 2);
      t0 *= 0.25f; t1 *= 0.25f;
      q0 = __uint_as_float(sv.y) + 144.f * (m0 - t0) * (m0 - t0); q1 = __uint_as_float(sv.w) + 144.f * (m1 - t1) * (m1 - t1);
      q0 += __shfl_xor_sync(~0u, q0, 1); q1 += __shfl_xor_sync(~0u, q1, 1);
      q0 += __shfl_xor_sync(~0u, q0, 2); q1 += __shfl_xor_sync(~0u, q1, 2);
      const float r0 = rsqrtf(q0 * (1.f / 576) + 1e-5f), r1 = rsqrtf(q1 * (1.f / 576) + 1e-5f);
      uint32_t* px = (uint32_t*)&g_xnB[st][seg][0] + (c * 18 * 4 + rb * 2) * 32 + lane;
#pragma unroll
      for (int jn = 0; jn < 18; jn++) {
        px[jn * 128] = pk((acc[4 * jn] - t0) * r0, (acc[4 * jn + 1] - t0) * r0);
        px[jn * 128 + 32] = pk((acc[4 * jn + 2] - t1) * r1, (acc[4 * jn + 3] - t1) * r1);
      }
      flag_add(&g_fXB[st][seg][0]);
    }
    GT(n, 2);
  }
}

__global__ void __launch_bounds__(256, 1)
g_kernel(const bf16* __restrict__ x, const bf16* __restrict__ wqkv, const bf16* __restrict__ wo, const bf16* __restrict__ Wo, bf16* __restrict__ out) {
  extern __shared__ __align__(1024) uint8_t smraw[];
  const uint32_t sb = smem_u32(smraw);
  const uint32_t epoch = *(volatile uint32_t*)&g_epoch;
  const int b = blockIdx.x;
  if (b < G_W) role_W(smraw, sb, b, epoch, x, Wo, out);
  else if (b < G_W + G_AQ) role_AQ(smraw, sb, b - G_W, epoch, wqkv);
  else role_AO(smraw, sb, b - G_W - G_AQ, epoch, wo);
}

extern "C" void kernel_launch(void* const* d_in, const int* in_sizes, int n_in, void* d_out, int out_size) {
  const bf16 *x = (const bf16*)d_in[0], *wqkv = (const bf16*)d_in[1], *wo = (const bf16*)d_in[2], *mem0 = (const bf16*)d_in[4];
  const bf16 *Wq = (const bf16*)d_in[5], *Wk = (const bf16*)d_in[6], *Wv = (const bf16*)d_in[7], *Wo = (const bf16*)d_in[8];
  cudaFuncSetAttribute(h_kernel, cudaFuncAttributeMaxDynamicSharedMemorySize, H_SMEM);
  cudaFuncSetAttribute(g_kernel, cudaFuncAttributeMaxDynamicSharedMemorySize, G_SMEM);
  cudaStream_t st = cudaStreamPerThread;
  h_kernel<<<96, 384, H_SMEM, st>>>(Wq, Wk, Wv, Wo, mem0);
  cudaLaunchConfig_t cfg = {};
  cfg.gridDim = dim3(G_W + G_AQ + G_AO); cfg.blockDim = dim3(256); cfg.dynamicSmemBytes = G_SMEM; cfg.stream = st;
  cudaLaunchAttribute at[1];
  at[0].id = cudaLaunchAttributeProgrammaticStreamSerialization; at[0].val.programmaticStreamSerializationAllowed = 1;
  cfg.attrs = at; cfg.numAttrs = 1;
  cudaLaunchKernelEx(&cfg, g_kernel, x, wqkv, wo, Wo, (bf16*)d_out);
}
```

```cpp
#include <cuda_runtime.h>
#include <cuda_bf16.h>
#include <stdint.h>
typedef __nv_bfloat16 bf16;

#define LAG 8
#define EX 2
#define N2 2
#ifndef NV
#define NV 20
#endif
#define PD 900
#define OD 1000
#define FM 3
#define RD 300
#define FB 0
#define PDS 150
#define PDJ 0
#define N1 4
#define NS 0
#define PF 0
#define PFD 0
#define PFW 0
#define VW 1
constexpr int NSEG = 64;
constexpr int NSTEP = NSEG + LAG;
constexpr int LEAD = LAG + 2;
constexpr int ORING = 16, PRING = 16;

__device__ uint4 g_xr[4][NSEG][2304];
__device__ float4 g_stA[2][NSEG][2][18][8];
__device__ uint4 g_oA[2][NSEG][2304];
__device__ uint4 g_xnB[2][NSEG][2304];
__device__ uint4 g_O[3][ORING][2][256][32];
__device__ uint4 g_P[2][PRING][7][2][36][32];
__device__ uint4 g_stat[2][NSEG][2][32];
__device__ uint4 g_acc[4][1536];
__device__ uint32_t g_fXA[2][NSEG][2][8], g_fOA[2][NSEG][2][8], g_fXB[2][NSEG][8];
__device__ uint32_t g_fO[2][NSEG][32];
__device__ uint32_t g_epoch;
#define TR(i)
#define TRW(i, ww)
#define GT(n, i)

#define OPAQUE(x) asm volatile("" : "+r"(x))
template<int N> __device__ __forceinline__ void pin(float* a) {
#pragma unroll
  for (int i = 0; i < N; i++) asm volatile("" : "+f"(a[i]) :: "memory");
}
__device__ __forceinline__ int lane_id() { int l; asm volatile("mov.u32 %0, %%laneid;" : "=r"(l)); return l; }
constexpr uint32_t SPIN_MAX = 4000000;
__device__ __forceinline__ uint32_t smem_u32(const void* p) { return (uint32_t)__cvta_generic_to_shared(p); }
__device__ __forceinline__ void mbar_init(uint32_t mb, uint32_t n) { asm volatile("mbarrier.init.shared::cta.b64 [%0], %1;" :: "r"(mb), "r"(n) : "memory"); }
__device__ __forceinline__ void mbar_expect(uint32_t mb, uint32_t bytes) { asm volatile("mbarrier.arrive.expect_tx.shared::cta.b64 _, [%0], %1;" :: "r"(mb), "r"(bytes) : "memory"); }
__device__ __forceinline__ void mbar_arrive(uint32_t mb) { asm volatile("mbarrier.arrive.shared::cta.b64 _, [%0];" :: "r"(mb) : "memory"); }
__device__ __forceinline__ void mbar_wait(uint32_t mb, uint32_t par) {
  asm volatile("{.reg .pred p; .reg .u32 c;\n"
               "mbarrier.try_wait.parity.shared::cta.b64 p, [%0], %1; @p bra.uni D_%=; mov.u32 c, 0;\n"
               "W_%=: mbarrier.try_wait.parity.shared::cta.b64 p, [%0], %1; @p bra.uni D_%=;\n"
               "add.u32 c, c, 1; setp.lt.u32 p, c, 4000000; @p bra.uni W_%=; trap;\n"
               "D_%=: }" :: "r"(mb), "r"(par) : "memory");
}
__device__ __forceinline__ void st_async1(uint32_t a, uint32_t v, uint32_t mb) {
  asm volatile("st.async.weak.shared::cluster.mbarrier::complete_tx::bytes.b32 [%0], %1, [%2];" :: "r"(a), "r"(v), "r"(mb) : "memory");
}
__device__ __forceinline__ void st_async4(uint32_t a, uint32_t x, uint32_t y, uint32_t z, uint32_t w, uint32_t mb) {
  asm volatile("st.async.weak.shared::cluster.mbarrier::complete_tx::bytes.v4.b32 [%0], {%1,%2,%3,%4}, [%5];" :: "r"(a), "r"(x), "r"(y), "r"(z), "r"(w), "r"(mb) : "memory");
}
__device__ __forceinline__ void fence_async() { asm volatile("fence.proxy.async.shared::cta;" ::: "memory"); }
__device__ __forceinline__ void publish(uint32_t mb, uint32_t zero_addr, int lane) {
  asm volatile("{.reg .pred p; .reg .b32 x; ld.volatile.shared.b32 x, [%1]; setp.eq.u32 p, x, %2;\n"
               "@p mbarrier.arrive.shared::cta.b64 _, [%0];}" :: "r"(mb), "r"(zero_addr), "r"(lane) : "memory");
}
__device__ __forceinline__ void fence_gpu() { asm volatile("fence.acq_rel.gpu;" ::: "memory"); }
__device__ __forceinline__ void wg_fence() { asm volatile("wgmma.fence.sync.aligned;" ::: "memory"); }
__device__ __forceinline__ void wg_commit() { asm volatile("wgmma.commit_group.sync.aligned;" ::: "memory"); }
template<int N> __device__ __forceinline__ void wg_wait() { asm volatile("wgmma.wait_group.sync.aligned %0;" :: "n"(N) : "memory"); }
__device__ __forceinline__ uint32_t pk(float a, float b) { uint32_t r; asm("cvt.rn.bf16x2.f32 %0, %1, %2;" : "=r"(r) : "f"(b), "f"(a)); return r; }
__device__ __forceinline__ float blo(uint32_t v) { return __uint_as_float(v << 16); }
__device__ __forceinline__ float bhi(uint32_t v) { return __uint_as_float(v & 0xFFFF0000u); }
__device__ __forceinline__ float ex2(float x) { float y; asm("ex2.approx.ftz.f32 %0, %1;" : "=f"(y) : "f"(x)); return y; }
__device__ __forceinline__ float rcp(float x) { float y; asm("rcp.approx.ftz.f32 %0, %1;" : "=f"(y) : "f"(x)); return y; }
__device__ __forceinline__ uint64_t mkdesc(uint32_t addr, uint32_t lbo, uint32_t sbo) {
  return (uint64_t)((addr & 0x3FFFF) >> 4) | ((uint64_t)(lbo >> 4) << 16) | ((uint64_t)(sbo >> 4) << 32);
}
__device__ __forceinline__ void cp16(uint32_t dst, const void* src) { asm volatile("cp.async.cg.shared.global [%0], [%1], 16;" :: "r"(dst), "l"(src) : "memory"); }
__device__ __forceinline__ void cp4(uint32_t dst, const void* src) { asm volatile("cp.async.ca.shared.global [%0], [%1], 4;" :: "r"(dst), "l"(src) : "memory"); }
__device__ __forceinline__ void cp_wait_all() { asm volatile("cp.async.commit_group; cp.async.wait_group 0;" ::: "memory"); }
__device__ __forceinline__ void ldsm4(uint32_t* r, uint32_t addr) {
  asm volatile("ldmatrix.sync.aligned.m8n8.x4.shared.b16 {%0,%1,%2,%3}, [%4];" : "=r"(r[0]), "=r"(r[1]), "=r"(r[2]), "=r"(r[3]) : "r"(addr) : "memory");
}
__device__ __forceinline__ void ldsm2(uint32_t* r, uint32_t addr) {
  asm volatile("ldmatrix.sync.aligned.m8n8.x2.shared.b16 {%0,%1}, [%2];" : "=r"(r[0]), "=r"(r[1]) : "r"(addr) : "memory");
}
__device__ __forceinline__ void ldsm4t(uint32_t* r, uint32_t addr) {
  asm volatile("ldmatrix.sync.aligned.m8n8.x4.trans.shared.b16 {%0,%1,%2,%3}, [%4];" : "=r"(r[0]), "=r"(r[1]), "=r"(r[2]), "=r"(r[3]) : "r"(addr) : "memory");
}
__device__ __forceinline__ void bulk_g2s(uint32_t dst, const void* src, uint32_t bytes, uint32_t mb) {
  asm volatile("cp.async.bulk.shared::cluster.global.mbarrier::complete_tx::bytes [%0], [%1], %2, [%3];" :: "r"(dst), "l"(src), "r"(bytes), "r"(mb) : "memory");
}
__device__ __forceinline__ void bulk_s2g(void* dst, uint32_t src, uint32_t bytes) {
  asm volatile("cp.async.bulk.global.shared::cta.bulk_group [%0], [%1], %2; cp.async.bulk.commit_group;" :: "l"(dst), "r"(src), "r"(bytes) : "memory");
}
__device__ __forceinline__ void bulk_s2s(uint32_t dst, uint32_t src, uint32_t mb) {
  asm volatile("cp.async.bulk.shared::cluster.shared::cta.mbarrier::complete_tx::bytes [%0], [%1], 8192, [%2];" :: "r"(dst), "r"(src), "r"(mb) : "memory");
}
__device__ __forceinline__ void l2_prefetch(const void* p, uint32_t bytes) { asm volatile("cp.async.bulk.prefetch.L2.global [%0], %1;" :: "l"(p), "r"(bytes) : "memory"); }
__device__ __forceinline__ uint32_t ld_acq(const uint32_t* p) { uint32_t v; asm volatile("ld.acquire.gpu.global.u32 %0, [%1];" : "=r"(v) : "l"(p) : "memory"); return v; }
__device__ __forceinline__ uint4 ld_rlx(const uint4* p) {
  uint4 v; asm volatile("ld.relaxed.gpu.global.v4.b32 {%0,%1,%2,%3}, [%4];" : "=r"(v.x), "=r"(v.y), "=r"(v.z), "=r"(v.w) : "l"(p) : "memory"); return v;
}
__device__ __forceinline__ void ld_rlx(uint32_t* r, const uint4* p) {
  asm volatile("ld.relaxed.gpu.global.v4.b32 {%0,%1,%2,%3}, [%4];" : "=r"(r[0]), "=r"(r[1]), "=r"(r[2]), "=r"(r[3]) : "l"(p) : "memory");
}
__device__ __forceinline__ void st_rlx(uint4* p, uint4 v) {
  asm volatile("st.relaxed.gpu.global.v4.b32 [%0], {%1,%2,%3,%4};" :: "l"(p), "r"(v.x), "r"(v.y), "r"(v.z), "r"(v.w) : "memory");
}
__device__ __forceinline__ void red4(uint4* p, uint32_t a, uint32_t b, uint32_t c, bool on) {
  asm volatile("{.reg .pred p; setp.ne.u32 p, %5, 0; @p red.relaxed.gpu.global.add.noftz.v4.bf16x2 [%0], {%1,%2,%3,%4};}"
               :: "l"(p), "r"(a), "r"(b), "r"(c), "r"(0x3F80u), "r"((uint32_t)on) : "memory");
}
__device__ __forceinline__ void stsm4(uint32_t a, uint32_t x, uint32_t y, uint32_t z, uint32_t w) {
  asm volatile("stmatrix.sync.aligned.m8n8.x4.shared.b16 [%0], {%1,%2,%3,%4};" :: "r"(a), "r"(x), "r"(y), "r"(z), "r"(w) : "memory");
}
__device__ __forceinline__ uint32_t movt(uint32_t v) { uint32_t r; asm volatile("movmatrix.sync.aligned.m8n8.trans.b16 %0, %1;" : "=r"(r) : "r"(v)); return r; }
__device__ __forceinline__ void sts1(uint32_t a, uint32_t v) { asm volatile("st.shared.b32 [%0], %1;" :: "r"(a), "r"(v) : "memory"); }
__device__ __forceinline__ void sts4(uint32_t a, uint32_t x, uint32_t y, uint32_t z, uint32_t w) { asm volatile("st.shared.v4.b32 [%0], {%1,%2,%3,%4};" :: "r"(a), "r"(x), "r"(y), "r"(z), "r"(w) : "memory"); }
__device__ __forceinline__ void flag_wait(const uint32_t* p, uint32_t target) {
  uint32_t it = 0;
  while (ld_acq(p) != target) { if (FB > 0) __nanosleep(FB); if (++it > SPIN_MAX) __trap(); }
}
__device__ __forceinline__ void flag_add(uint32_t* p) {
  fence_gpu();
  __syncwarp();
  if ((threadIdx.x & 31) == 0) asm volatile("red.relaxed.gpu.global.add.u32 [%0], 1;" :: "l"(p) : "memory");
}
#define HMMA(d, a0, a1, a2, a3, b0, b1) asm volatile("mma.sync.aligned.m16n8k16.row.col.f32.bf16.bf16.f32 {%0,%1,%2,%3},{%4,%5,%6,%7},{%8,%9},{%0,%1,%2,%3};" \
  : "+f"((d)[0]), "+f"((d)[1]), "+f"((d)[2]), "+f"((d)[3]) : "r"(a0), "r"(a1), "r"(a2), "r"(a3), "r"(b0), "r"(b1))
#define HMMA8(d, a0, a1, b0) asm volatile("mma.sync.aligned.m16n8k8.row.col.f32.bf16.bf16.f32 {%0,%1,%2,%3},{%4,%5},{%6},{%0,%1,%2,%3};" \
  : "+f"((d)[0]), "+f"((d)[1]), "+f"((d)[2]), "+f"((d)[3]) : "r"(a0), "r"(a1), "r"(b0))

template<int ACC> __device__ __forceinline__ void rs24(float* d, const uint32_t* a, uint64_t b) {
  if (ACC) asm volatile("wgmma.mma_async.sync.aligned.m64n24k16.f32.bf16.bf16 {%0,%1,%2,%3,%4,%5,%6,%7,%8,%9,%10,%11},{%12,%13,%14,%15},%16,1,1,1,0;"
    : "+f"(d[0]), "+f"(d[1]), "+f"(d[2]), "+f"(d[3]), "+f"(d[4]), "+f"(d[5]), "+f"(d[6]), "+f"(d[7]), "+f"(d[8]), "+f"(d[9]), "+f"(d[10]), "+f"(d[11])
    : "r"(a[0]), "r"(a[1]), "r"(a[2]), "r"(a[3]), "l"(b));
  else asm volatile("wgmma.mma_async.sync.aligned.m64n24k16.f32.bf16.bf16 {%0,%1,%2,%3,%4,%5,%6,%7,%8,%9,%10,%11},{%12,%13,%14,%15},%16,0,1,1,0;"
    : "=f"(d[0]), "=f"(d[1]), "=f"(d[2]), "=f"(d[3]), "=f"(d[4]), "=f"(d[5]), "=f"(d[6]), "=f"(d[7]), "=f"(d[8]), "=f"(d[9]), "=f"(d[10]), "=f"(d[11])
    : "r"(a[0]), "r"(a[1]), "r"(a[2]), "r"(a[3]), "l"(b));
}

template<int ACC> __device__ __forceinline__ void rs32(float* d, const uint32_t* a, uint64_t b) {
  if (ACC) asm volatile("wgmma.mma_async.sync.aligned.m64n32k16.f32.bf16.bf16 {%0,%1,%2,%3,%4,%5,%6,%7,%8,%9,%10,%11,%12,%13,%14,%15},{%16,%17,%18,%19},%20,1,1,1,0;"
    : "+f"(d[0]), "+f"(d[1]), "+f"(d[2]), "+f"(d[3]), "+f"(d[4]), "+f"(d[5]), "+f"(d[6]), "+f"(d[7]), "+f"(d[8]), "+f"(d[9]), "+f"(d[10]), "+f"(d[11]),
      "+f"(d[12]), "+f"(d[13]), "+f"(d[14]), "+f"(d[15])
    : "r"(a[0]), "r"(a[1]), "r"(a[2]), "r"(a[3]), "l"(b));
  else asm volatile("wgmma.mma_async.sync.aligned.m64n32k16.f32.bf16.bf16 {%0,%1,%2,%3,%4,%5,%6,%7,%8,%9,%10,%11,%12,%13,%14,%15},{%16,%17,%18,%19},%20,0,1,1,0;"
    : "=f"(d[0]), "=f"(d[1]), "=f"(d[2]), "=f"(d[3]), "=f"(d[4]), "=f"(d[5]), "=f"(d[6]), "=f"(d[7]), "=f"(d[8]), "=f"(d[9]), "=f"(d[10]), "=f"(d[11]),
      "=f"(d[12]), "=f"(d[13]), "=f"(d[14]), "=f"(d[15])
    : "r"(a[0]), "r"(a[1]), "r"(a[2]), "r"(a[3]), "l"(b));
}

template<int ACC> __device__ __forceinline__ void rs48(float* d, const uint32_t* a, uint64_t b) {
  if (ACC) asm volatile("wgmma.mma_async.sync.aligned.m64n48k16.f32.bf16.bf16 {%0,%1,%2,%3,%4,%5,%6,%7,%8,%9,%10,%11,%12,%13,%14,%15,%16,%17,%18,%19,%20,%21,%22,%23},{%24,%25,%26,%27},%28,1,1,1,0;"
    : "+f"(d[0]), "+f"(d[1]), "+f"(d[2]), "+f"(d[3]), "+f"(d[4]), "+f"(d[5]), "+f"(d[6]), "+f"(d[7]), "+f"(d[8]), "+f"(d[9]), "+f"(d[10]), "+f"(d[11]),
      "+f"(d[12]), "+f"(d[13]), "+f"(d[14]), "+f"(d[15]), "+f"(d[16]), "+f"(d[17]), "+f"(d[18]), "+f"(d[19]), "+f"(d[20]), "+f"(d[21]), "+f"(d[22]), "+f"(d[23])
    : "r"(a[0]), "r"(a[1]), "r"(a[2]), "r"(a[3]), "l"(b));
  else asm volatile("wgmma.mma_async.sync.aligned.m64n48k16.f32.bf16.bf16 {%0,%1,%2,%3,%4,%5,%6,%7,%8,%9,%10,%11,%12,%13,%14,%15,%16,%17,%18,%19,%20,%21,%22,%23},{%24,%25,%26,%27},%28,0,1,1,0;"
    : "=f"(d[0]), "=f"(d[1]), "=f"(d[2]), "=f"(d[3]), "=f"(d[4]), "=f"(d[5]), "=f"(d[6]), "=f"(d[7]), "=f"(d[8]), "=f"(d[9]), "=f"(d[10]), "=f"(d[11]),
      "=f"(d[12]), "=f"(d[13]), "=f"(d[14]), "=f"(d[15]), "=f"(d[16]), "=f"(d[17]), "=f"(d[18]), "=f"(d[19]), "=f"(d[20]), "=f"(d[21]), "=f"(d[22]), "=f"(d[23])
    : "r"(a[0]), "r"(a[1]), "r"(a[2]), "r"(a[3]), "l"(b));
}

template<int ACC> __device__ __forceinline__ void rs56(float* d, const uint32_t* a, uint64_t b) {
  if (ACC) asm volatile("wgmma.mma_async.sync.aligned.m64n56k16.f32.bf16.bf16 {%0,%1,%2,%3,%4,%5,%6,%7,%8,%9,%10,%11,%12,%13,%14,%15,%16,%17,%18,%19,%20,%21,%22,%23,%24,%25,%26,%27},{%28,%29,%30,%31},%32,1,1,1,0;"
    : "+f"(d[0]), "+f"(d[1]), "+f"(d[2]), "+f"(d[3]), "+f"(d[4]), "+f"(d[5]), "+f"(d[6]), "+f"(d[7]), "+f"(d[8]), "+f"(d[9]), "+f"(d[10]), "+f"(d[11]),
      "+f"(d[12]), "+f"(d[13]), "+f"(d[14]), "+f"(d[15]), "+f"(d[16]), "+f"(d[17]), "+f"(d[18]), "+f"(d[19]), "+f"(d[20]), "+f"(d[21]), "+f"(d[22]), "+f"(d[23]),
      "+f"(d[24]), "+f"(d[25]), "+f"(d[26]), "+f"(d[27])
    : "r"(a[0]), "r"(a[1]), "r"(a[2]), "r"(a[3]), "l"(b));
  else asm volatile("wgmma.mma_async.sync.aligned.m64n56k16.f32.bf16.bf16 {%0,%1,%2,%3,%4,%5,%6,%7,%8,%9,%10,%11,%12,%13,%14,%15,%16,%17,%18,%19,%20,%21,%22,%23,%24,%25,%26,%27},{%28,%29,%30,%31},%32,0,1,1,0;"
    : "=f"(d[0]), "=f"(d[1]), "=f"(d[2]), "=f"(d[3]), "=f"(d[4]), "=f"(d[5]), "=f"(d[6]), "=f"(d[7]), "=f"(d[8]), "=f"(d[9]), "=f"(d[10]), "=f"(d[11]),
      "=f"(d[12]), "=f"(d[13]), "=f"(d[14]), "=f"(d[15]), "=f"(d[16]), "=f"(d[17]), "=f"(d[18]), "=f"(d[19]), "=f"(d[20]), "=f"(d[21]), "=f"(d[22]), "=f"(d[23]),
      "=f"(d[24]), "=f"(d[25]), "=f"(d[26]), "=f"(d[27])
    : "r"(a[0]), "r"(a[1]), "r"(a[2]), "r"(a[3]), "l"(b));
}

template<int ACC> __device__ __forceinline__ void rs64(float* d, const uint32_t* a, uint64_t b) {
  if (ACC) asm volatile("wgmma.mma_async.sync.aligned.m64n64k16.f32.bf16.bf16 {%0,%1,%2,%3,%4,%5,%6,%7,%8,%9,%10,%11,%12,%13,%14,%15,%16,%17,%18,%19,%20,%21,%22,%23,%24,%25,%26,%27,%28,%29,%30,%31},{%32,%33,%34,%35},%36,1,1,1,0;"
    : "+f"(d[0]), "+f"(d[1]), "+f"(d[2]), "+f"(d[3]), "+f"(d[4]), "+f"(d[5]), "+f"(d[6]), "+f"(d[7]), "+f"(d[8]), "+f"(d[9]), "+f"(d[10]), "+f"(d[11]),
      "+f"(d[12]), "+f"(d[13]), "+f"(d[14]), "+f"(d[15]), "+f"(d[16]), "+f"(d[17]), "+f"(d[18]), "+f"(d[19]), "+f"(d[20]), "+f"(d[21]), "+f"(d[22]), "+f"(d[23]),
      "+f"(d[24]), "+f"(d[25]), "+f"(d[26]), "+f"(d[27]), "+f"(d[28]), "+f"(d[29]), "+f"(d[30]), "+f"(d[31])
    : "r"(a[0]), "r"(a[1]), "r"(a[2]), "r"(a[3]), "l"(b));
  else asm volatile("wgmma.mma_async.sync.aligned.m64n64k16.f32.bf16.bf16 {%0,%1,%2,%3,%4,%5,%6,%7,%8,%9,%10,%11,%12,%13,%14,%15,%16,%17,%18,%19,%20,%21,%22,%23,%24,%25,%26,%27,%28,%29,%30,%31},{%32,%33,%34,%35},%36,0,1,1,0;"
    : "=f"(d[0]), "=f"(d[1]), "=f"(d[2]), "=f"(d[3]), "=f"(d[4]), "=f"(d[5]), "=f"(d[6]), "=f"(d[7]), "=f"(d[8]), "=f"(d[9]), "=f"(d[10]), "=f"(d[11]),
      "=f"(d[12]), "=f"(d[13]), "=f"(d[14]), "=f"(d[15]), "=f"(d[16]), "=f"(d[17]), "=f"(d[18]), "=f"(d[19]), "=f"(d[20]), "=f"(d[21]), "=f"(d[22]), "=f"(d[23]),
      "=f"(d[24]), "=f"(d[25]), "=f"(d[26]), "=f"(d[27]), "=f"(d[28]), "=f"(d[29]), "=f"(d[30]), "=f"(d[31])
    : "r"(a[0]), "r"(a[1]), "r"(a[2]), "r"(a[3]), "l"(b));
}

template<int ACC> __device__ __forceinline__ void ss24tn(float* d, uint64_t a, uint64_t b) {
  if (ACC) asm volatile("wgmma.mma_async.sync.aligned.m64n24k16.f32.bf16.bf16 {%0,%1,%2,%3,%4,%5,%6,%7,%8,%9,%10,%11},%12,%13,1,1,1,1,0;"
    : "+f"(d[0]), "+f"(d[1]), "+f"(d[2]), "+f"(d[3]), "+f"(d[4]), "+f"(d[5]), "+f"(d[6]), "+f"(d[7]), "+f"(d[8]), "+f"(d[9]), "+f"(d[10]), "+f"(d[11])
    : "l"(a), "l"(b));
  else asm volatile("wgmma.mma_async.sync.aligned.m64n24k16.f32.bf16.bf16 {%0,%1,%2,%3,%4,%5,%6,%7,%8,%9,%10,%11},%12,%13,0,1,1,1,0;"
    : "=f"(d[0]), "=f"(d[1]), "=f"(d[2]), "=f"(d[3]), "=f"(d[4]), "=f"(d[5]), "=f"(d[6]), "=f"(d[7]), "=f"(d[8]), "=f"(d[9]), "=f"(d[10]), "=f"(d[11])
    : "l"(a), "l"(b));
}

template<int ACC> __device__ __forceinline__ void ss32tn(float* d, uint64_t a, uint64_t b) {
  if (ACC) asm volatile("wgmma.mma_async.sync.aligned.m64n32k16.f32.bf16.bf16 {%0,%1,%2,%3,%4,%5,%6,%7,%8,%9,%10,%11,%12,%13,%14,%15},%16,%17,1,1,1,1,0;"
    : "+f"(d[0]), "+f"(d[1]), "+f"(d[2]), "+f"(d[3]), "+f"(d[4]), "+f"(d[5]), "+f"(d[6]), "+f"(d[7]), "+f"(d[8]), "+f"(d[9]), "+f"(d[10]), "+f"(d[11]),
      "+f"(d[12]), "+f"(d[13]), "+f"(d[14]), "+f"(d[15])
    : "l"(a), "l"(b));
  else asm volatile("wgmma.mma_async.sync.aligned.m64n32k16.f32.bf16.bf16 {%0,%1,%2,%3,%4,%5,%6,%7,%8,%9,%10,%11,%12,%13,%14,%15},%16,%17,0,1,1,1,0;"
    : "=f"(d[0]), "=f"(d[1]), "=f"(d[2]), "=f"(d[3]), "=f"(d[4]), "=f"(d[5]), "=f"(d[6]), "=f"(d[7]), "=f"(d[8]), "=f"(d[9]), "=f"(d[10]), "=f"(d[11]),
      "=f"(d[12]), "=f"(d[13]), "=f"(d[14]), "=f"(d[15])
    : "l"(a), "l"(b));
}

template<int ACC> __device__ __forceinline__ void ss48tn(float* d, uint64_t a, uint64_t b) {
  if (ACC) asm volatile("wgmma.mma_async.sync.aligned.m64n48k16.f32.bf16.bf16 {%0,%1,%2,%3,%4,%5,%6,%7,%8,%9,%10,%11,%12,%13,%14,%15,%16,%17,%18,%19,%20,%21,%22,%23},%24,%25,1,1,1,1,0;"
    : "+f"(d[0]), "+f"(d[1]), "+f"(d[2]), "+f"(d[3]), "+f"(d[4]), "+f"(d[5]), "+f"(d[6]), "+f"(d[7]), "+f"(d[8]), "+f"(d[9]), "+f"(d[10]), "+f"(d[11]),
      "+f"(d[12]), "+f"(d[13]), "+f"(d[14]), "+f"(d[15]), "+f"(d[16]), "+f"(d[17]), "+f"(d[18]), "+f"(d[19]), "+f"(d[20]), "+f"(d[21]), "+f"(d[22]), "+f"(d[23])
    : "l"(a), "l"(b));
  else asm volatile("wgmma.mma_async.sync.aligned.m64n48k16.f32.bf16.bf16 {%0,%1,%2,%3,%4,%5,%6,%7,%8,%9,%10,%11,%12,%13,%14,%15,%16,%17,%18,%19,%20,%21,%22,%23},%24,%25,0,1,1,1,0;"
    : "=f"(d[0]), "=f"(d[1]), "=f"(d[2]), "=f"(d[3]), "=f"(d[4]), "=f"(d[5]), "=f"(d[6]), "=f"(d[7]), "=f"(d[8]), "=f"(d[9]), "=f"(d[10]), "=f"(d[11]),
      "=f"(d[12]), "=f"(d[13]), "=f"(d[14]), "=f"(d[15]), "=f"(d[16]), "=f"(d[17]), "=f"(d[18]), "=f"(d[19]), "=f"(d[20]), "=f"(d[21]), "=f"(d[22]), "=f"(d[23])
    : "l"(a), "l"(b));
}

template<int ACC> __device__ __forceinline__ void ss56tn(float* d, uint64_t a, uint64_t b) {
  if (ACC) asm volatile("wgmma.mma_async.sync.aligned.m64n56k16.f32.bf16.bf16 {%0,%1,%2,%3,%4,%5,%6,%7,%8,%9,%10,%11,%12,%13,%14,%15,%16,%17,%18,%19,%20,%21,%22,%23,%24,%25,%26,%27},%28,%29,1,1,1,1,0;"
    : "+f"(d[0]), "+f"(d[1]), "+f"(d[2]), "+f"(d[3]), "+f"(d[4]), "+f"(d[5]), "+f"(d[6]), "+f"(d[7]), "+f"(d[8]), "+f"(d[9]), "+f"(d[10]), "+f"(d[11]),
      "+f"(d[12]), "+f"(d[13]), "+f"(d[14]), "+f"(d[15]), "+f"(d[16]), "+f"(d[17]), "+f"(d[18]), "+f"(d[19]), "+f"(d[20]), "+f"(d[21]), "+f"(d[22]), "+f"(d[23]),
      "+f"(d[24]), "+f"(d[25]), "+f"(d[26]), "+f"(d[27])
    : "l"(a), "l"(b));
  else asm volatile("wgmma.mma_async.sync.aligned.m64n56k16.f32.bf16.bf16 {%0,%1,%2,%3,%4,%5,%6,%7,%8,%9,%10,%11,%12,%13,%14,%15,%16,%17,%18,%19,%20,%21,%22,%23,%24,%25,%26,%27},%28,%29,0,1,1,1,0;"
    : "=f"(d[0]), "=f"(d[1]), "=f"(d[2]), "=f"(d[3]), "=f"(d[4]), "=f"(d[5]), "=f"(d[6]), "=f"(d[7]), "=f"(d[8]), "=f"(d[9]), "=f"(d[10]), "=f"(d[11]),
      "=f"(d[12]), "=f"(d[13]), "=f"(d[14]), "=f"(d[15]), "=f"(d[16]), "=f"(d[17]), "=f"(d[18]), "=f"(d[19]), "=f"(d[20]), "=f"(d[21]), "=f"(d[22]), "=f"(d[23]),
      "=f"(d[24]), "=f"(d[25]), "=f"(d[26]), "=f"(d[27])
    : "l"(a), "l"(b));
}

template<int ACC> __device__ __forceinline__ void ss40tt(float* d, uint64_t a, uint64_t b) {
  if (ACC) asm volatile("wgmma.mma_async.sync.aligned.m64n40k16.f32.bf16.bf16 {%0,%1,%2,%3,%4,%5,%6,%7,%8,%9,%10,%11,%12,%13,%14,%15,%16,%17,%18,%19},%20,%21,1,1,1,1,1;"
    : "+f"(d[0]), "+f"(d[1]), "+f"(d[2]), "+f"(d[3]), "+f"(d[4]), "+f"(d[5]), "+f"(d[6]), "+f"(d[7]), "+f"(d[8]), "+f"(d[9]), "+f"(d[10]), "+f"(d[11]),
      "+f"(d[12]), "+f"(d[13]), "+f"(d[14]), "+f"(d[15]), "+f"(d[16]), "+f"(d[17]), "+f"(d[18]), "+f"(d[19])
    : "l"(a), "l"(b));
  else asm volatile("wgmma.mma_async.sync.aligned.m64n40k16.f32.bf16.bf16 {%0,%1,%2,%3,%4,%5,%6,%7,%8,%9,%10,%11,%12,%13,%14,%15,%16,%17,%18,%19},%20,%21,0,1,1,1,1;"
    : "=f"(d[0]), "=f"(d[1]), "=f"(d[2]), "=f"(d[3]), "=f"(d[4]), "=f"(d[5]), "=f"(d[6]), "=f"(d[7]), "=f"(d[8]), "=f"(d[9]), "=f"(d[10]), "=f"(d[11]),
      "=f"(d[12]), "=f"(d[13]), "=f"(d[14]), "=f"(d[15]), "=f"(d[16]), "=f"(d[17]), "=f"(d[18]), "=f"(d[19])
    : "l"(a), "l"(b));
}

template<int ACC> __device__ __forceinline__ void rs144t(float* d, const uint32_t* a, uint64_t b) {
  if (ACC) asm volatile("wgmma.mma_async.sync.aligned.m64n144k16.f32.bf16.bf16 {%0,%1,%2,%3,%4,%5,%6,%7,%8,%9,%10,%11,%12,%13,%14,%15,%16,%17,%18,%19,%20,%21,%22,%23,%24,%25,%26,%27,%28,%29,%30,%31,%32,%33,%34,%35,%36,%37,%38,%39,%40,%41,%42,%43,%44,%45,%46,%47,%48,%49,%50,%51,%52,%53,%54,%55,%56,%57,%58,%59,%60,%61,%62,%63,%64,%65,%66,%67,%68,%69,%70,%71},{%72,%73,%74,%75},%76,1,1,1,1;"
    : "+f"(d[0]), "+f"(d[1]), "+f"(d[2]), "+f"(d[3]), "+f"(d[4]), "+f"(d[5]), "+f"(d[6]), "+f"(d[7]), "+f"(d[8]), "+f"(d[9]), "+f"(d[10]), "+f"(d[11]),
      "+f"(d[12]), "+f"(d[13]), "+f"(d[14]), "+f"(d[15]), "+f"(d[16]), "+f"(d[17]), "+f"(d[18]), "+f"(d[19]), "+f"(d[20]), "+f"(d[21]), "+f"(d[22]), "+f"(d[23]),
      "+f"(d[24]), "+f"(d[25]), "+f"(d[26]), "+f"(d[27]), "+f"(d[28]), "+f"(d[29]), "+f"(d[30]), "+f"(d[31]), "+f"(d[32]), "+f"(d[33]), "+f"(d[34]), "+f"(d[35]),
      "+f"(d[36]), "+f"(d[37]), "+f"(d[38]), "+f"(d[39]), "+f"(d[40]), "+f"(d[41]), "+f"(d[42]), "+f"(d[43]), "+f"(d[44]), "+f"(d[45]), "+f"(d[46]), "+f"(d[47]),
      "+f"(d[48]), "+f"(d[49]), "+f"(d[50]), "+f"(d[51]), "+f"(d[52]), "+f"(d[53]), "+f"(d[54]), "+f"(d[55]), "+f"(d[56]), "+f"(d[57]), "+f"(d[58]), "+f"(d[59]),
      "+f"(d[60]), "+f"(d[61]), "+f"(d[62]), "+f"(d[63]), "+f"(d[64]), "+f"(d[65]), "+f"(d[66]), "+f"(d[67]), "+f"(d[68]), "+f"(d[69]), "+f"(d[70]), "+f"(d[71])
    : "r"(a[0]), "r"(a[1]), "r"(a[2]), "r"(a[3]), "l"(b));
  else asm volatile("wgmma.mma_async.sync.aligned.m64n144k16.f32.bf16.bf16 {%0,%1,%2,%3,%4,%5,%6,%7,%8,%9,%10,%11,%12,%13,%14,%15,%16,%17,%18,%19,%20,%21,%22,%23,%24,%25,%26,%27,%28,%29,%30,%31,%32,%33,%34,%35,%36,%37,%38,%39,%40,%41,%42,%43,%44,%45,%46,%47,%48,%49,%50,%51,%52,%53,%54,%55,%56,%57,%58,%59,%60,%61,%62,%63,%64,%65,%66,%67,%68,%69,%70,%71},{%72,%73,%74,%75},%76,0,1,1,1;"
    : "=f"(d[0]), "=f"(d[1]), "=f"(d[2]), "=f"(d[3]), "=f"(d[4]), "=f"(d[5]), "=f"(d[6]), "=f"(d[7]), "=f"(d[8]), "=f"(d[9]), "=f"(d[10]), "=f"(d[11]),
      "=f"(d[12]), "=f"(d[13]), "=f"(d[14]), "=f"(d[15]), "=f"(d[16]), "=f"(d[17]), "=f"(d[18]), "=f"(d[19]), "=f"(d[20]), "=f"(d[21]), "=f"(d[22]), "=f"(d[23]),
      "=f"(d[24]), "=f"(d[25]), "=f"(d[26]), "=f"(d[27]), "=f"(d[28]), "=f"(d[29]), "=f"(d[30]), "=f"(d[31]), "=f"(d[32]), "=f"(d[33]), "=f"(d[34]), "=f"(d[35]),
      "=f"(d[36]), "=f"(d[37]), "=f"(d[38]), "=f"(d[39]), "=f"(d[40]), "=f"(d[41]), "=f"(d[42]), "=f"(d[43]), "=f"(d[44]), "=f"(d[45]), "=f"(d[46]), "=f"(d[47]),
      "=f"(d[48]), "=f"(d[49]), "=f"(d[50]), "=f"(d[51]), "=f"(d[52]), "=f"(d[53]), "=f"(d[54]), "=f"(d[55]), "=f"(d[56]), "=f"(d[57]), "=f"(d[58]), "=f"(d[59]),
      "=f"(d[60]), "=f"(d[61]), "=f"(d[62]), "=f"(d[63]), "=f"(d[64]), "=f"(d[65]), "=f"(d[66]), "=f"(d[67]), "=f"(d[68]), "=f"(d[69]), "=f"(d[70]), "=f"(d[71])
    : "r"(a[0]), "r"(a[1]), "r"(a[2]), "r"(a[3]), "l"(b));
}

template<int ACC> __device__ __forceinline__ void rs168t(float* d, const uint32_t* a, uint64_t b) {
  if (ACC) asm volatile("wgmma.mma_async.sync.aligned.m64n168k16.f32.bf16.bf16 {%0,%1,%2,%3,%4,%5,%6,%7,%8,%9,%10,%11,%12,%13,%14,%15,%16,%17,%18,%19,%20,%21,%22,%23,%24,%25,%26,%27,%28,%29,%30,%31,%32,%33,%34,%35,%36,%37,%38,%39,%40,%41,%42,%43,%44,%45,%46,%47,%48,%49,%50,%51,%52,%53,%54,%55,%56,%57,%58,%59,%60,%61,%62,%63,%64,%65,%66,%67,%68,%69,%70,%71,%72,%73,%74,%75,%76,%77,%78,%79,%80,%81,%82,%83},{%84,%85,%86,%87},%88,1,1,1,1;"
    : "+f"(d[0]), "+f"(d[1]), "+f"(d[2]), "+f"(d[3]), "+f"(d[4]), "+f"(d[5]), "+f"(d[6]), "+f"(d[7]), "+f"(d[8]), "+f"(d[9]), "+f"(d[10]), "+f"(d[11]),
      "+f"(d[12]), "+f"(d[13]), "+f"(d[14]), "+f"(d[15]), "+f"(d[16]), "+f"(d[17]), "+f"(d[18]), "+f"(d[19]), "+f"(d[20]), "+f"(d[21]), "+f"(d[22]), "+f"(d[23]),
      "+f"(d[24]), "+f"(d[25]), "+f"(d[26]), "+f"(d[27]), "+f"(d[28]), "+f"(d[29]), "+f"(d[30]), "+f"(d[31]), "+f"(d[32]), "+f"(d[33]), "+f"(d[34]), "+f"(d[35]),
      "+f"(d[36]), "+f"(d[37]), "+f"(d[38]), "+f"(d[39]), "+f"(d[40]), "+f"(d[41]), "+f"(d[42]), "+f"(d[43]), "+f"(d[44]), "+f"(d[45]), "+f"(d[46]), "+f"(d[47]),
      "+f"(d[48]), "+f"(d[49]), "+f"(d[50]), "+f"(d[51]), "+f"(d[52]), "+f"(d[53]), "+f"(d[54]), "+f"(d[55]), "+f"(d[56]), "+f"(d[57]), "+f"(d[58]), "+f"(d[59]),
      "+f"(d[60]), "+f"(d[61]), "+f"(d[62]), "+f"(d[63]), "+f"(d[64]), "+f"(d[65]), "+f"(d[66]), "+f"(d[67]), "+f"(d[68]), "+f"(d[69]), "+f"(d[70]), "+f"(d[71]),
      "+f"(d[72]), "+f"(d[73]), "+f"(d[74]), "+f"(d[75]), "+f"(d[76]), "+f"(d[77]), "+f"(d[78]), "+f"(d[79]), "+f"(d[80]), "+f"(d[81]), "+f"(d[82]), "+f"(d[83])
    : "r"(a[0]), "r"(a[1]), "r"(a[2]), "r"(a[3]), "l"(b));
  else asm volatile("wgmma.mma_async.sync.aligned.m64n168k16.f32.bf16.bf16 {%0,%1,%2,%3,%4,%5,%6,%7,%8,%9,%10,%11,%12,%13,%14,%15,%16,%17,%18,%19,%20,%21,%22,%23,%24,%25,%26,%27,%28,%29,%30,%31,%32,%33,%34,%35,%36,%37,%38,%39,%40,%41,%42,%43,%44,%45,%46,%47,%48,%49,%50,%51,%52,%53,%54,%55,%56,%57,%58,%59,%60,%61,%62,%63,%64,%65,%66,%67,%68,%69,%70,%71,%72,%73,%74,%75,%76,%77,%78,%79,%80,%81,%82,%83},{%84,%85,%86,%87},%88,0,1,1,1;"
    : "=f"(d[0]), "=f"(d[1]), "=f"(d[2]), "=f"(d[3]), "=f"(d[4]), "=f"(d[5]), "=f"(d[6]), "=f"(d[7]), "=f"(d[8]), "=f"(d[9]), "=f"(d[10]), "=f"(d[11]),
      "=f"(d[12]), "=f"(d[13]), "=f"(d[14]), "=f"(d[15]), "=f"(d[16]), "=f"(d[17]), "=f"(d[18]), "=f"(d[19]), "=f"(d[20]), "=f"(d[21]), "=f"(d[22]), "=f"(d[23]),
      "=f"(d[24]), "=f"(d[25]), "=f"(d[26]), "=f"(d[27]), "=f"(d[28]), "=f"(d[29]), "=f"(d[30]), "=f"(d[31]), "=f"(d[32]), "=f"(d[33]), "=f"(d[34]), "=f"(d[35]),
      "=f"(d[36]), "=f"(d[37]), "=f"(d[38]), "=f"(d[39]), "=f"(d[40]), "=f"(d[41]), "=f"(d[42]), "=f"(d[43]), "=f"(d[44]), "=f"(d[45]), "=f"(d[46]), "=f"(d[47]),
      "=f"(d[48]), "=f"(d[49]), "=f"(d[50]), "=f"(d[51]), "=f"(d[52]), "=f"(d[53]), "=f"(d[54]), "=f"(d[55]), "=f"(d[56]), "=f"(d[57]), "=f"(d[58]), "=f"(d[59]),
      "=f"(d[60]), "=f"(d[61]), "=f"(d[62]), "=f"(d[63]), "=f"(d[64]), "=f"(d[65]), "=f"(d[66]), "=f"(d[67]), "=f"(d[68]), "=f"(d[69]), "=f"(d[70]), "=f"(d[71]),
      "=f"(d[72]), "=f"(d[73]), "=f"(d[74]), "=f"(d[75]), "=f"(d[76]), "=f"(d[77]), "=f"(d[78]), "=f"(d[79]), "=f"(d[80]), "=f"(d[81]), "=f"(d[82]), "=f"(d[83])
    : "r"(a[0]), "r"(a[1]), "r"(a[2]), "r"(a[3]), "l"(b));
}

template<int ACC> __device__ __forceinline__ void rs192t(float* d, const uint32_t* a, uint64_t b) {
  if (ACC) asm volatile("wgmma.mma_async.sync.aligned.m64n192k16.f32.bf16.bf16 {%0,%1,%2,%3,%4,%5,%6,%7,%8,%9,%10,%11,%12,%13,%14,%15,%16,%17,%18,%19,%20,%21,%22,%23,%24,%25,%26,%27,%28,%29,%30,%31,%32,%33,%34,%35,%36,%37,%38,%39,%40,%41,%42,%43,%44,%45,%46,%47,%48,%49,%50,%51,%52,%53,%54,%55,%56,%57,%58,%59,%60,%61,%62,%63,%64,%65,%66,%67,%68,%69,%70,%71,%72,%73,%74,%75,%76,%77,%78,%79,%80,%81,%82,%83,%84,%85,%86,%87,%88,%89,%90,%91,%92,%93,%94,%95},{%96,%97,%98,%99},%100,1,1,1,1;"
    : "+f"(d[0]), "+f"(d[1]), "+f"(d[2]), "+f"(d[3]), "+f"(d[4]), "+f"(d[5]), "+f"(d[6]), "+f"(d[7]), "+f"(d[8]), "+f"(d[9]), "+f"(d[10]), "+f"(d[11]),
      "+f"(d[12]), "+f"(d[13]), "+f"(d[14]), "+f"(d[15]), "+f"(d[16]), "+f"(d[17]), "+f"(d[18]), "+f"(d[19]), "+f"(d[20]), "+f"(d[21]), "+f"(d[22]), "+f"(d[23]),
      "+f"(d[24]), "+f"(d[25]), "+f"(d[26]), "+f"(d[27]), "+f"(d[28]), "+f"(d[29]), "+f"(d[30]), "+f"(d[31]), "+f"(d[32]), "+f"(d[33]), "+f"(d[34]), "+f"(d[35]),
      "+f"(d[36]), "+f"(d[37]), "+f"(d[38]), "+f"(d[39]), "+f"(d[40]), "+f"(d[41]), "+f"(d[42]), "+f"(d[43]), "+f"(d[44]), "+f"(d[45]), "+f"(d[46]), "+f"(d[47]),
      "+f"(d[48]), "+f"(d[49]), "+f"(d[50]), "+f"(d[51]), "+f"(d[52]), "+f"(d[53]), "+f"(d[54]), "+f"(d[55]), "+f"(d[56]), "+f"(d[57]), "+f"(d[58]), "+f"(d[59]),
      "+f"(d[60]), "+f"(d[61]), "+f"(d[62]), "+f"(d[63]), "+f"(d[64]), "+f"(d[65]), "+f"(d[66]), "+f"(d[67]), "+f"(d[68]), "+f"(d[69]), "+f"(d[70]), "+f"(d[71]),
      "+f"(d[72]), "+f"(d[73]), "+f"(d[74]), "+f"(d[75]), "+f"(d[76]), "+f"(d[77]), "+f"(d[78]), "+f"(d[79]), "+f"(d[80]), "+f"(d[81]), "+f"(d[82]), "+f"(d[83]),
      "+f"(d[84]), "+f"(d[85]), "+f"(d[86]), "+f"(d[87]), "+f"(d[88]), "+f"(d[89]), "+f"(d[90]), "+f"(d[91]), "+f"(d[92]), "+f"(d[93]), "+f"(d[94]), "+f"(d[95])
    : "r"(a[0]), "r"(a[1]), "r"(a[2]), "r"(a[3]), "l"(b));
  else asm volatile("wgmma.mma_async.sync.aligned.m64n192k16.f32.bf16.bf16 {%0,%1,%2,%3,%4,%5,%6,%7,%8,%9,%10,%11,%12,%13,%14,%15,%16,%17,%18,%19,%20,%21,%22,%23,%24,%25,%26,%27,%28,%29,%30,%31,%32,%33,%34,%35,%36,%37,%38,%39,%40,%41,%42,%43,%44,%45,%46,%47,%48,%49,%50,%51,%52,%53,%54,%55,%56,%57,%58,%59,%60,%61,%62,%63,%64,%65,%66,%67,%68,%69,%70,%71,%72,%73,%74,%75,%76,%77,%78,%79,%80,%81,%82,%83,%84,%85,%86,%87,%88,%89,%90,%91,%92,%93,%94,%95},{%96,%97,%98,%99},%100,0,1,1,1;"
    : "=f"(d[0]), "=f"(d[1]), "=f"(d[2]), "=f"(d[3]), "=f"(d[4]), "=f"(d[5]), "=f"(d[6]), "=f"(d[7]), "=f"(d[8]), "=f"(d[9]), "=f"(d[10]), "=f"(d[11]),
      "=f"(d[12]), "=f"(d[13]), "=f"(d[14]), "=f"(d[15]), "=f"(d[16]), "=f"(d[17]), "=f"(d[18]), "=f"(d[19]), "=f"(d[20]), "=f"(d[21]), "=f"(d[22]), "=f"(d[23]),
      "=f"(d[24]), "=f"(d[25]), "=f"(d[26]), "=f"(d[27]), "=f"(d[28]), "=f"(d[29]), "=f"(d[30]), "=f"(d[31]), "=f"(d[32]), "=f"(d[33]), "=f"(d[34]), "=f"(d[35]),
      "=f"(d[36]), "=f"(d[37]), "=f"(d[38]), "=f"(d[39]), "=f"(d[40]), "=f"(d[41]), "=f"(d[42]), "=f"(d[43]), "=f"(d[44]), "=f"(d[45]), "=f"(d[46]), "=f"(d[47]),
      "=f"(d[48]), "=f"(d[49]), "=f"(d[50]), "=f"(d[51]), "=f"(d[52]), "=f"(d[53]), "=f"(d[54]), "=f"(d[55]), "=f"(d[56]), "=f"(d[57]), "=f"(d[58]), "=f"(d[59]),
      "=f"(d[60]), "=f"(d[61]), "=f"(d[62]), "=f"(d[63]), "=f"(d[64]), "=f"(d[65]), "=f"(d[66]), "=f"(d[67]), "=f"(d[68]), "=f"(d[69]), "=f"(d[70]), "=f"(d[71]),
      "=f"(d[72]), "=f"(d[73]), "=f"(d[74]), "=f"(d[75]), "=f"(d[76]), "=f"(d[77]), "=f"(d[78]), "=f"(d[79]), "=f"(d[80]), "=f"(d[81]), "=f"(d[82]), "=f"(d[83]),
      "=f"(d[84]), "=f"(d[85]), "=f"(d[86]), "=f"(d[87]), "=f"(d[88]), "=f"(d[89]), "=f"(d[90]), "=f"(d[91]), "=f"(d[92]), "=f"(d[93]), "=f"(d[94]), "=f"(d[95])
    : "r"(a[0]), "r"(a[1]), "r"(a[2]), "r"(a[3]), "l"(b));
}

constexpr uint32_t PL = 9216;
constexpr uint32_t H_MEM = 0, H_QB = 92160, H_KB = 102400, H_VB = 112640, H_ZERO = H_VB + 10240, H_OS = 124928, H_ST = 133120, H_OM = 141312,
                   H_WO = 147712, H_WL = 196864, H_DUMP = 209152, H_BAR = 209280, H_TRC = 145408;
constexpr uint32_t H_SMEM = 209536;
constexpr int KR = 33 + EX;
constexpr uint32_t WLS = (36 - KR) * 256;
constexpr int NM = 16 + 8 * EX, NB = 64 - 8 * EX;
constexpr uint32_t B_MEM = H_BAR, B_XT = H_BAR + 32, B_XB = H_BAR + 40, B_MD = H_BAR + 48, B_QK = H_BAR + 64, B_V = H_BAR + 72,
                   B_OM = H_BAR + 80, B_W2 = H_BAR + 88, B_W3 = H_BAR + 96, B_OS = H_BAR + 104, B_ST = H_BAR + 112, B_XA = H_BAR + 120, B_WS = H_BAR + 56, B_XC = H_BAR + 128;

__device__ __forceinline__ void cluster_sync() { asm volatile("barrier.cluster.arrive.release.aligned; barrier.cluster.wait.acquire.aligned;" ::: "memory"); }

template<int N, int KK> __device__ __forceinline__ void proj_step(float* acc, const uint32_t* w, uint64_t d, uint64_t wl) {
  constexpr int A = KK > 0;
  if constexpr (KK < KR) {
    if (N == 24) rs24<A>(acc, &w[KK * 4], d + KK * 16); if (N == 32) rs32<A>(acc, &w[KK * 4], d + KK * 16);
    if (N == 48) rs48<A>(acc, &w[KK * 4], d + KK * 16); if (N == 56) rs56<A>(acc, &w[KK * 4], d + KK * 16);
  } else {
    if (N == 24) ss24tn<1>(acc, wl + (KK - KR) * 16, d + KK * 16); if (N == 32) ss32tn<1>(acc, wl + (KK - KR) * 16, d + KK * 16);
    if (N == 48) ss48tn<1>(acc, wl + (KK - KR) * 16, d + KK * 16); if (N == 56) ss56tn<1>(acc, wl + (KK - KR) * 16, d + KK * 16);
  }
}
template<int N, int K0, int K1> __device__ __forceinline__ void proj_loop(float* acc, const uint32_t* w, uint64_t d, uint64_t wl) {
  if constexpr (K0 < K1) { proj_step<N, K0>(acc, w, d, wl); proj_loop<N, K0 + 1, K1>(acc, w, d, wl); }
}
template<int N, int K0, int K1> __device__ __forceinline__ void proj_steps(float* acc, const uint32_t* w, uint64_t d, uint64_t wl) {
  if constexpr (K0 < K1) { wg_fence(); proj_loop<N, K0, K1>(acc, w, d, wl); wg_commit(); }
}

template<int J> __device__ __forceinline__ void h_proj(const uint32_t sb, const int wg, const int w, const int lane) {
  uint32_t wr[KR * 4];
  {
    const uint32_t a = sb + (wg * 8 + w * 2 + ((lane >> 3) & 1)) * 9232 + ((lane >> 4) * 8 + (lane & 7)) * 16;
#pragma unroll
    for (int kk = 0; kk < KR; kk++) ldsm4t(&wr[kk * 4], a + kk * 256);
  }
  asm volatile("bar.sync 1, 512;" ::: "memory");
  cluster_sync();
  constexpr uint32_t BUF = J == 0 ? H_QB : J == 1 ? H_KB : H_VB, BAR = J == 2 ? B_V : B_QK;
  const uint32_t so = sb & 0x1FFFFFF;
  const uint32_t dst = so + BUF + 8192 + (wg * 8 + w * 2) * 128 + lane * 4;
  const uint64_t wl = mkdesc(sb + H_WL + wg * 8 * WLS, 128, WLS);
  const uint64_t md = mkdesc(sb + H_MEM, 128, PL);
  uint32_t pt[2 * EX];
  auto put = [&](const uint32_t* p) {
    const uint32_t a = sb + (wg * 8 + w * 2) * 128 + (lane >> 3) * 2048 + (lane & 7) * 16;
#pragma unroll
    for (int L = 0; L < 2; L++) {
      const uint32_t b = a + (J == 2 ? (L ? H_KB : H_QB) : L == J ? BUF : H_ST);
      stsm4(b, p[8 * L], p[8 * L + 2], p[8 * L + 4], p[8 * L + 6]);
      stsm4(b + 128, p[8 * L + 1], p[8 * L + 3], p[8 * L + 5], p[8 * L + 7]);
    }
    publish(sb + B_ST, sb + H_ZERO, lane);
  };
  {
    float acc[16];
    mbar_wait(sb + B_XB, 0);
    proj_steps<32, 0, 36>(acc, wr, md + 6 * (PL / 16), wl);
    wg_wait<0>(); pin<16>(acc);
    uint32_t p[16];
#pragma unroll
    for (int i = 0; i < 8; i++) p[i] = p[8 + i] = pk(acc[2 * i], acc[2 * i + 1]);
    put(p);
  }
  for (int s = 0;; s++) {
    float accM[NM / 2], accB[NB / 2];
    mbar_wait(sb + B_XT, s & 1);
    mbar_wait(sb + B_MEM, s & 1);
    if (wg == 0) { TR(0); }
    proj_steps<NM, 0, 9>(accM, wr, md, wl);
    mbar_wait(sb + B_MEM + 8, s & 1);
    proj_steps<NM, 9, 18>(accM, wr, md, wl);
    mbar_wait(sb + B_MEM + 16, s & 1);
    proj_steps<NM, 18, 27>(accM, wr, md, wl);
    mbar_wait(sb + B_MEM + 24, s & 1);
    if (lane == 0) mbar_arrive(sb + B_XC);
    if (wg == 0) { TR(6); }
    proj_steps<NM, 27, 36>(accM, wr, md, wl);
    wg_wait<0>(); pin<NM / 2>(accM);
#pragma unroll
    for (int L = 0; L < 2; L++) if (L != J) {
      st_async1(dst + (L << 25), pk(accM[4 * L], accM[4 * L + 1]), so + BAR + (L << 25));
      st_async1(dst + (L << 25) + 128, pk(accM[4 * L + 2], accM[4 * L + 3]), so + BAR + (L << 25));
    }
    if (J < 2) {
      sts1(dst + (J << 25), pk(accM[4 * J], accM[4 * J + 1])); sts1(dst + (J << 25) + 128, pk(accM[4 * J + 2], accM[4 * J + 3]));
      publish(sb + B_QK, sb + H_ZERO, lane);
    }
    TR(1 + wg * 4);
    if (s == NSTEP - 1) break;
    if (lane == 0) mbar_arrive(sb + B_MD);
#pragma unroll
    for (int i = 0; i < 2 * EX; i++) pt[i] = pk(accM[8 + 2 * i], accM[9 + 2 * i]);
    const uint64_t bd = md + (2 + EX) * (PL / 16);
    constexpr int NA = J < 2 ? N1 + NS + N2 : NV;
    mbar_wait(sb + B_XA, s & 1);
    proj_steps<NB, 0, N1>(accB, wr, bd, wl);
    if (J < 2 && NS > 0) mbar_wait(sb + B_WS, s & 1);
    proj_steps<NB, N1, N1 + NS>(accB, wr, bd, wl);
    if (J < 2 && N2 > 0) mbar_wait(sb + B_W2, s & 1);
    mbar_wait(sb + B_XB, (s + 1) & 1);
    proj_steps<NB, N1 + NS, NA>(accB, wr, bd, wl);
    mbar_wait(sb + B_W3, s & 1);
    if (wg == 0) { TR(2); }
    proj_steps<NB, NA, 36>(accB, wr, bd, wl);
    wg_wait<0>(); pin<NB / 2>(accB);
    if (wg == 0) { TR(3); }
    uint32_t p[16];
#pragma unroll
    for (int i = 0; i < 16; i++) p[i] = i < 2 * EX ? pt[i] : pk(accB[2 * (i - 2 * EX)], accB[2 * (i - 2 * EX) + 1]);
    put(p);
  }
}

template<int J> __device__ __forceinline__ void h_chain(uint8_t* smraw, const uint32_t sb, const int w, int lane, const uint32_t epoch, const bf16* __restrict__ mem0) {
  asm volatile("bar.sync 1, 512;" ::: "memory");
#pragma unroll 1
  for (int i = w * 144 + lane; i < w * 144 + 144; i += 32) {
    const uint4 v = *(const uint4*)(mem0 + (i & 7) * 576 + (i >> 3) * 8);
    *(uint4*)(smraw + H_MEM + i * 16) = v; *(uint4*)(smraw + H_MEM + PL + i * 16) = v;
  }
  *(uint4*)(smraw + H_ZERO + (w * 32 + lane) * 16) = make_uint4(0, 0, 0, 0);
  asm volatile("bar.sync 2, 128;" ::: "memory");
  fence_async();
  __syncwarp();
  if (lane == 0) mbar_arrive(sb + B_MEM + w * 8);
  cluster_sync();
  const uint32_t so = sb & 0x1FFFFFF;
  uint32_t ring = (epoch * (NSTEP - 1)) & 3;
  for (int s = 0;; s++) {
    const uint32_t par = s & 1;
    lane = lane_id();
    const float cs = 0.08838834764831845f * 1.4426950408889634f;
    const uint32_t wb = sb + H_WO + w * 6 * 2048 + lane * 16;
    uint32_t bq[4][12];
    if (J < 2) {
      float sc[20];
      uint32_t pa[12];
      asm volatile("ld.shared.v2.b32 {%0,%1}, [%2];" : "=r"(pa[10]), "=r"(pa[11]) : "r"(sb + H_ZERO));
      const uint64_t qd = mkdesc(sb + H_QB, 128, 2048), kd = mkdesc(sb + H_KB, 128, 2048), vd = mkdesc(sb + H_VB, 2048, 128);
      mbar_wait(sb + B_QK, par);
      TR(8);
      wg_fence();
#pragma unroll
      for (int kk = 0; kk < 8; kk++) { if (kk == 0) ss40tt<0>(sc, qd, kd); else ss40tt<1>(sc, qd + kk * 16, kd + kk * 16); }
      wg_commit();
      if (VW == 0) mbar_wait(sb + B_V, par);
      wg_wait<0>(); pin<20>(sc);
      if (NS > 0 && w == 3 && lane == 0) mbar_arrive(sb + B_WS);
      TR(7);
      float s0 = 0.f, s1 = 0.f;
      if (w < 2) {
        const int r0 = (lane >> 2) * 2 + w - 4 * (lane & 3);
        float m0 = fmaxf(sc[16], sc[17]), m1 = fmaxf(sc[18], sc[19]);
#pragma unroll
        for (int i = 0; i < 4; i += 2) {
          const int c = i >> 1;
          const bool k0 = c > r0, k1 = c + 2 > r0;
          if (k0) { sc[4 * i] = -INFINITY; sc[4 * i + 6] = -INFINITY; }
          if (k1) { sc[4 * i + 1] = -INFINITY; sc[4 * i + 7] = -INFINITY; }
          m0 = fmaxf(m0, fmaxf(sc[4 * i], sc[4 * i + 1]));
          m1 = fmaxf(m1, fmaxf(fmaxf(sc[4 * i + 2], sc[4 * i + 3]), fmaxf(sc[4 * i + 6], sc[4 * i + 7])));
        }
        m1 = fmaxf(m1, __shfl_xor_sync(~0u, m1, 1)); m0 = fmaxf(m0, __shfl_xor_sync(~0u, m0, 1));
        m1 = fmaxf(m1, __shfl_xor_sync(~0u, m1, 2)); m0 = fmaxf(m0, __shfl_xor_sync(~0u, m0, 2));
        m0 *= cs; m1 *= cs;
#pragma unroll
        for (int i = 0; i < 5; i++) {
          if (i & 1) pa[2 * i] = pa[10];
          else {
            const float a = ex2(fmaf(sc[4 * i], cs, -m0)), b = ex2(fmaf(sc[4 * i + 1], cs, -m0));
            s0 += a + b; pa[2 * i] = pk(a, b);
          }
          const float a = ex2(fmaf(sc[4 * i + 2], cs, -m1)), b = ex2(fmaf(sc[4 * i + 3], cs, -m1));
          s1 += a + b; pa[2 * i + 1] = pk(a, b);
        }
      } else {
        float m0 = fmaxf(fmaxf(fmaxf(sc[0], sc[1]), fmaxf(sc[4], sc[5])), fmaxf(fmaxf(fmaxf(sc[8], sc[9]), fmaxf(sc[12], sc[13])), fmaxf(sc[16], sc[17])));
        m0 = fmaxf(m0, __shfl_xor_sync(~0u, m0, 1));
        m0 = fmaxf(m0, __shfl_xor_sync(~0u, m0, 2));
        m0 *= cs;
#pragma unroll
        for (int i = 0; i < 5; i++) {
          const float a = ex2(fmaf(sc[4 * i], cs, -m0)), b = ex2(fmaf(sc[4 * i + 1], cs, -m0));
          s0 += a + b; pa[2 * i] = pk(a, b); pa[2 * i + 1] = pa[10];
        }
        if (VW == 1) mbar_wait(sb + B_V, par);
      }
      TR(4);
      float o[2][32];
      wg_fence();
      rs64<0>(o[0], pa, vd); rs64<1>(o[0], pa + 4, vd + 256); rs64<1>(o[0], pa + 8, vd + 512); wg_commit();
      rs64<0>(o[1], pa, vd + 64); rs64<1>(o[1], pa + 4, vd + 64 + 256); rs64<1>(o[1], pa + 8, vd + 64 + 512); wg_commit();
      s0 += __shfl_xor_sync(~0u, s0, 1); s1 += __shfl_xor_sync(~0u, s1, 1);
      s0 += __shfl_xor_sync(~0u, s0, 2); s1 += __shfl_xor_sync(~0u, s1, 2);
      s0 = rcp(s0); s1 = rcp(s1);
      if (w == 2 && s < NSTEP - 1) {
        const uint32_t omo = so + H_OM + J * 2048 + (lane & 3) * 128 + (((lane >> 2) ^ ((lane & 3) * 2)) * 16);
        constexpr uint32_t R1 = (uint32_t)(1 - J) << 25, R2 = 2u << 25, RL = (uint32_t)J << 25;
        uint32_t x[16];
#pragma unroll
        for (int hf = 0; hf < 2; hf++) {
          if (hf == 0) wg_wait<1>(); else wg_wait<0>();
          pin<32>(o[hf]);
#pragma unroll
          for (int jg = 2 * hf; jg < 2 * hf + 2; jg++) {
#pragma unroll
            for (int i = 0; i < 4; i++) x[4 * jg + i] = pk(o[hf][(jg & 1) * 16 + 4 * i] * s0, o[hf][(jg & 1) * 16 + 4 * i + 1] * s0);
            st_async4(omo + jg * 512 + R1, x[4 * jg], x[4 * jg + 1], x[4 * jg + 2], x[4 * jg + 3], so + B_OM + R1);
            st_async4(omo + jg * 512 + R2, x[4 * jg], x[4 * jg + 1], x[4 * jg + 2], x[4 * jg + 3], so + B_OM + R2);
          }
        }
#pragma unroll
        for (int jg = 0; jg < 4; jg++) sts4(omo + jg * 512 + RL, x[4 * jg], x[4 * jg + 1], x[4 * jg + 2], x[4 * jg + 3]);
        __syncwarp();
        if (lane == 0) { mbar_arrive(sb + B_OM); if (N2 > 0) mbar_arrive(sb + B_W2); }
        TRW(9, 2);
      } else {
        wg_wait<0>();
        pin<32>(o[0]); pin<32>(o[1]);
        if (w < 2) {
          const uint32_t os = sb + H_OS + w * 4096 + lane * 16;
#pragma unroll
          for (int kk = 0; kk < 8; kk++) {
            const float* oo = &o[kk >> 2][(kk & 3) * 8];
            sts4(os + kk * 512, pk(oo[0] * s0, oo[1] * s0), pk(oo[2] * s1, oo[3] * s1), pk(oo[4] * s0, oo[5] * s0), pk(oo[6] * s1, oo[7] * s1));
          }
        }
      }
    }
#pragma unroll
    for (int u = 0; u < 4; u++)
#pragma unroll
      for (int tt = 0; tt < 3; tt++) ldsm4t(&bq[u][tt * 4], wb + tt * 2048 + u * 512);
    const bool u0 = s < NSEG - 1, u1 = s >= LAG;
    uint4* const gacc = &g_acc[0][0] + ring * 1536;
    if (s < NSTEP - 1) {
      uint4* const pacc = gacc + ((w >> 1) * 384 + J * 64 + (w & 1) * 32 + lane);
      const uint32_t oa = sb + H_OM + ((lane >> 3) & 1) * 2048 + (lane >> 4) * 128 + (((lane & 7) ^ ((lane >> 4) * 2)) * 16);
      mbar_wait(sb + B_OM, par);
      TR(10);
      uint32_t A[8][4];
#pragma unroll
      for (int kk = 0; kk < 8; kk++) ldsm4(A[kk], (oa ^ ((kk & 1) * 64)) + kk * 256);
#pragma unroll
      for (int a = 0; a < 2; a++) {
        float d[3][4];
#pragma unroll
        for (int tt = 0; tt < 3; tt++) { d[tt][0] = d[tt][1] = d[tt][2] = d[tt][3] = 0.f; }
#pragma unroll
        for (int jg = 0; jg < 4; jg++) {
          uint32_t* b = bq[jg];
#pragma unroll
          for (int tt = 0; tt < 3; tt++) HMMA(d[tt], A[2 * jg][0], A[2 * jg][1], A[2 * jg][2], A[2 * jg][3], b[tt * 4], b[tt * 4 + 1]);
          if (a == 0 && jg > 0) {
#pragma unroll
            for (int tt = 0; tt < 3; tt++) ldsm4t(&bq[jg - 1][tt * 4], wb + (3 + tt) * 2048 + (jg - 1) * 512);
          }
          if (a == 1 && jg == 0) {
#pragma unroll
            for (int tt = 0; tt < 3; tt++) ldsm4t(&bq[3][tt * 4], wb + (3 + tt) * 2048 + 3 * 512);
          }
#pragma unroll
          for (int tt = 0; tt < 3; tt++) HMMA(d[tt], A[2 * jg + 1][0], A[2 * jg + 1][1], A[2 * jg + 1][2], A[2 * jg + 1][3], b[tt * 4 + 2], b[tt * 4 + 3]);
        }
        red4(pacc + a * 768, pk(d[0][0], d[0][1]), pk(d[1][0], d[1][1]), pk(d[2][0], d[2][1]), u0);
        red4(pacc + a * 768 + 192, pk(d[0][2], d[0][3]), pk(d[1][2], d[1][3]), pk(d[2][2], d[2][3]), u1);
      }
      if (lane == 0) mbar_arrive(sb + B_W3);
    }
    const uint32_t c0 = clock();
    TR(11);
    if (J < 2 && w < 2) { fence_async(); __syncwarp(); if (lane == 0) mbar_arrive(sb + B_OS); }
    if (s == NSTEP - 1) break;
    {
      const uint32_t ch = w ^ 2, lf = blockIdx.x & 1;
      const uint32_t la = (u0 && u1) ? lf : u1, lb = (u0 && u1) ? 1 - lf : u1;
      const uint4* const pa_ = gacc + (ch * 384 + la * 192 + lane);
      const uint4* const pb_ = gacc + (ch * 384 + lb * 192 + lane);
      const uint32_t ma = sb + H_MEM + la * PL + ch * 2304 + lane * 16, mb = sb + H_MEM + lb * PL + ch * 2304 + lane * 16;
      const uint32_t ma5 = lane < 24 ? ma + 1920 : sb + H_DUMP + (lane & 7) * 16, mb5 = lane < 24 ? mb + 1920 : ma5;
      const uint32_t dl = PD + (J == 2 ? PDJ : 0) + ch * PDS;
      while ((uint32_t)clock() - c0 < dl) {}
      uint32_t v[12][4];
      uint32_t it = 0;
      while (true) {
#pragma unroll
        for (int i = 0; i < 6; i++) { const int ii = (i + 2 * J) % 6; ld_rlx(v[ii], pa_ + ii * 32); ld_rlx(v[6 + ii], pb_ + ii * 32); }
        uint32_t mn = v[0][3];
#pragma unroll
        for (int i = 1; i < 12; i++) mn = min(mn, v[i][3]);
        if (__all_sync(~0u, mn == 0x4200u)) break;
        if (++it > SPIN_MAX) __trap();
      }
      TRW(12, 2);
#pragma unroll
      for (int i = 0; i < 6; i++) stsm4(i < 5 ? ma + i * 384 : ma5, v[i][0], v[i][1], v[i][2], v[i][3]);
#pragma unroll
      for (int i = 0; i < 6; i++) stsm4(i < 5 ? mb + i * 384 : mb5, v[6 + i][0], v[6 + i][1], v[6 + i][2], v[6 + i][3]);
      TRW(15, 2);
      publish(sb + B_MEM + ch * 8, sb + H_ZERO, lane);
    }
    ring = (ring + 1) & 3;
    TRW(14, 2);
  }
}

__device__ __forceinline__ uint32_t x_load(uint32_t sb, uint32_t bar, int L, int s, int p0, int p1, int d0, uint32_t o0, uint32_t o1, uint32_t epoch, bool wait) {
  const int seg = s - L * LAG;
  if ((uint32_t)seg >= (uint32_t)NSEG) return 0;
  if (wait) {
    flag_wait(&g_fXB[L][seg][0], (epoch + 1) * 8);
    asm volatile("fence.proxy.async.global;" ::: "memory");
  }
  const uint8_t* src = (const uint8_t*)&g_xnB[L][seg][p0 * 576] + o0;
  uint32_t dst = sb + H_MEM + d0 * PL + o0;
#pragma unroll 1
  for (int p = p0; p < p1; p++, src += PL, dst += PL) bulk_g2s(dst, src, o1 - o0, sb + bar);
  return (p1 - p0) * (o1 - o0);
}

__device__ __forceinline__ void h_help(const uint32_t sb, const int h, const int j, const int w, const int lane, const uint32_t epoch) {
  asm volatile("bar.sync 1, 512;" ::: "memory");
  cluster_sync();
  if (w == 0) {
    if (lane == 0) {
      constexpr uint32_t XS = (N1 + NS) * 256;
      mbar_expect(sb + B_XB, x_load(sb, B_XB, 0, 0, 0, 4, 6, 0, PL, epoch, true));
      mbar_expect(sb + B_XT, x_load(sb, B_XT, 0, 1, 0, EX, 2, 0, PL, epoch, true));
#pragma unroll 1
      for (int s = 0; s < NSTEP - 1; s++) {
        mbar_wait(sb + B_ST, s & 1);
        uint32_t n = x_load(sb, B_XA, 0, s + 1, EX, 4, 2 + EX, 0, XS, epoch, false);
        mbar_expect(sb + B_XA, n + x_load(sb, B_XA, 1, s + 1, 0, 4, 6, 0, XS, epoch, true));
        mbar_wait(sb + B_XC, s & 1);
        n = x_load(sb, B_XB, 0, s + 1, EX, 4, 2 + EX, XS, PL, epoch, false);
        mbar_expect(sb + B_XB, n + x_load(sb, B_XB, 1, s + 1, 0, 4, 6, XS, PL, epoch, false));
        mbar_wait(sb + B_MD, s & 1);
        mbar_expect(sb + B_XT, x_load(sb, B_XT, 0, s + 2, 0, EX, 2, 0, PL, epoch, true));
      }
    }
  } else if (w == 1) {
    if (lane == 0 && j < 2) {
#pragma unroll 1
      for (int s = 0; s < NSTEP; s++) {
        const int seg = s - j * LAG;
        mbar_wait(sb + B_OS, s & 1);
        mbar_expect(sb + B_QK, 10240);
        if ((uint32_t)seg < (uint32_t)NSEG) {
          if (OD > 0 && s < NSTEP - 1) __nanosleep(OD);
          uint4* po = &g_O[j][seg % ORING][0][8 * h][0];
          asm volatile("cp.async.bulk.global.shared::cta.bulk_group [%0], [%1], 4096;" :: "l"(po), "r"(sb + H_OS) : "memory");
          asm volatile("cp.async.bulk.global.shared::cta.bulk_group [%0], [%1], 4096;" :: "l"(po + 8192), "r"(sb + H_OS + 4096) : "memory");
          asm volatile("cp.async.bulk.commit_group; cp.async.bulk.wait_group.read 0;" ::: "memory");
          mbar_expect(sb + B_V, 10240);
          asm volatile("cp.async.bulk.wait_group 0; fence.proxy.async.global;" ::: "memory");
          asm volatile("st.release.gpu.global.u32 [%0], %1;" :: "l"(&g_fO[j][seg][h]), "r"(epoch + 1) : "memory");
        } else {
          mbar_expect(sb + B_V, 10240);
        }
      }
    }
  } else if (w == 2) {
    uint32_t ring = (epoch * (NSTEP - 1) + 3) & 3;
#pragma unroll 1
    for (int s = 0; s < NSTEP - 1; s++) {
      mbar_wait(sb + B_W3, s & 1);
      if (lane == 0) mbar_expect(sb + B_OM, j < 2 ? 2048 : 4096);
      mbar_wait(sb + B_MEM + 24, (s + 1) & 1);
      if (lane < 16) st_rlx(&g_acc[ring][blockIdx.x * 16 + lane], make_uint4(0, 0, 0, 0));
      ring = (ring + 1) & 3;
    }
  } else if (lane == 0) {
    const uint32_t so = sb & 0x1FFFFFF;
#pragma unroll 1
    for (int s = 0; s < NSTEP; s++) {
      mbar_wait(sb + B_ST, s & 1);
      if (j < 2) bulk_s2s(so + ((1 - j) << 25) + (j ? H_KB : H_QB), sb + H_ST, so + ((1 - j) << 25) + B_QK);
      else { bulk_s2s(so + H_VB, sb + H_QB, so + B_V); bulk_s2s(so + (1 << 25) + H_VB, sb + H_KB, so + (1 << 25) + B_V); }
    }
  }
  __syncwarp();
}

__global__ void __cluster_dims__(6, 1, 1) __launch_bounds__(512, 1)
h_kernel(const bf16* __restrict__ Wq, const bf16* __restrict__ Wk, const bf16* __restrict__ Wv, const bf16* __restrict__ Wo, const bf16* __restrict__ mem0,
         const bf16* __restrict__ x, const bf16* __restrict__ wqkv, const bf16* __restrict__ wo) {
  extern __shared__ __align__(1024) uint8_t smraw[];
  const uint32_t sb = smem_u32(smraw);
  const int j = (blockIdx.x % 6) >> 1, h = (blockIdx.x / 6) * 2 + (blockIdx.x & 1);
  const int tid = threadIdx.x, lane = tid & 31, w = __shfl_sync(~0u, (tid >> 5) & 3, 0), wg = __shfl_sync(~0u, tid >> 7, 0);
  asm volatile("griddepcontrol.launch_dependents;");
  if (PF > 0 && (tid & 127) == 0) {
    const int b = blockIdx.x;
    if (wg == 0) { l2_prefetch(wqkv + b * 10368, 20736); l2_prefetch(x + b * 1536, 3072); l2_prefetch(wo + b * 3456, 6912); l2_prefetch(x + 147456 + b * 10752, 21504); }
    if (PF > 1) { __nanosleep(PFD); l2_prefetch((wg == 0 ? Wo : wg == 1 ? Wq : wg == 2 ? Wk : Wv) + b * 24576, 49152); }
  }
  if (PFW > 0) __nanosleep(PFW);
  const uint32_t epoch = *(volatile uint32_t*)&g_epoch;
  {
    const bf16* W = (j == 0 ? Wq : j == 1 ? Wk : Wv) + h * 128;
    {
      const int c = tid & 15;
      const bf16* src = W + (size_t)(tid >> 4) * 4096 + c * 8;
#pragma unroll 1
      for (int kk = tid >> 4; kk < 576; kk += 32, src += 32 * 4096)
        cp16(kk < KR * 16 ? sb + c * 9232 + kk * 16 : sb + H_WL + c * WLS + (kk - KR * 16) * 16, src);
    }
    if (tid < 384) {
      const int d = tid / 24, ntl = tid % 24, ww = ntl / 6;
      const int p = 18 * (2 * ((ntl / 3) & 1) + (ww >> 1)) + 6 * j + 3 * (ww & 1) + ntl % 3;
      const bf16* Wh = Wo + (size_t)(h * 128 + d) * 576 + p * 8;
      const uint32_t dst = sb + H_WO + ntl * 2048 + (((d >> 1) & 3) * 8 + (d >> 3) * 2 + (d & 1)) * 16;
#pragma unroll
      for (int i = 0; i < 8; i++) cp16(dst + (i >> 1) * 512 + (i & 1) * 64, Wh + i * 16 * 576);
    }
    if (tid == 0) {
      for (int c = 0; c < 4; c++) mbar_init(sb + B_MEM + c * 8, 1);
      mbar_init(sb + B_XT, 1); mbar_init(sb + B_XA, 1); mbar_init(sb + B_WS, 1); mbar_init(sb + B_XC, 8); mbar_init(sb + B_XB, 1); mbar_init(sb + B_MD, 8); mbar_init(sb + B_ST, 8);
      mbar_init(sb + B_QK, 9); mbar_init(sb + B_V, 1); mbar_init(sb + B_OM, j < 2 ? 2 : 1); mbar_init(sb + B_OS, 2);
      mbar_init(sb + B_W2, 1); mbar_init(sb + B_W3, 4);
      mbar_expect(sb + B_QK, 10240); mbar_expect(sb + B_V, 10240);
      mbar_expect(sb + B_OM, j < 2 ? 2048 : 4096);
      asm volatile("fence.mbarrier_init.release.cluster;" ::: "memory");
    }
    cp_wait_all();
    fence_async();
    __syncthreads();
  }
  if (wg < 2) {
    asm volatile("setmaxnreg.inc.sync.aligned.u32 192;");
    if (j == 0) h_proj<0>(sb, wg, w, lane); else if (j == 1) h_proj<1>(sb, wg, w, lane); else h_proj<2>(sb, wg, w, lane);
    cluster_sync();
  } else if (wg == 2) {
    asm volatile("setmaxnreg.dec.sync.aligned.u32 104;");
    if (j == 0) h_chain<0>(smraw, sb, w, lane, epoch, mem0); else if (j == 1) h_chain<1>(smraw, sb, w, lane, epoch, mem0); else h_chain<2>(smraw, sb, w, lane, epoch, mem0);
    cluster_sync();
  } else {
    asm volatile("setmaxnreg.dec.sync.aligned.u32 24;");
    h_help(sb, h, j, w, lane, epoch);
    cluster_sync();
  }
}

constexpr int G_W = 21, G_AQ = 11, G_AO = 4;
constexpr uint32_t G_SMEM = 232448;

template<int N, int NK, class F> __device__ __forceinline__ void gemm_rs(float* acc, const uint4* pa, uint32_t baddr, F&& ready) {
  constexpr int G = (NK + 2) / 3;
  uint32_t a[2 * G * 4];
  const uint64_t bd = mkdesc(baddr, N * 16, 128);
  auto step = [&](int kk) {
    const int slot = kk % (2 * G);
    if (N == 192) { if (kk == 0) rs192t<0>(acc, &a[0], bd); else rs192t<1>(acc, &a[slot * 4], bd + kk * (N * 2)); }
    if (N == 168) { if (kk == 0) rs168t<0>(acc, &a[0], bd); else rs168t<1>(acc, &a[slot * 4], bd + kk * (N * 2)); }
    if (N == 144) { if (kk == 0) rs144t<0>(acc, &a[0], bd); else rs144t<1>(acc, &a[slot * 4], bd + kk * (N * 2)); }
  };
#pragma unroll
  for (int i = 0; i < 2 * G; i++) ld_rlx(&a[i * 4], pa + i * 32);
  ready();
  wg_fence();
  step(0); wg_commit();
  wg_wait<7>();
#pragma unroll
  for (int kk = 1; kk < G; kk++) step(kk);
  wg_commit();
  wg_fence();
  step(G); wg_commit();
  wg_wait<1>();
#pragma unroll
  for (int i = 2 * G; i < NK; i++) ld_rlx(&a[(i - 2 * G) * 4], pa + i * 32);
  wg_fence();
  step(G + 1); wg_commit();
  wg_wait<7>();
#pragma unroll
  for (int kk = G + 2; kk < 2 * G; kk++) step(kk);
  wg_commit();
  wg_fence();
#pragma unroll
  for (int kk = 2 * G; kk < NK; kk++) step(kk);
  wg_commit();
  wg_wait<0>();
  pin<N / 2>(acc);
}

__device__ __forceinline__ void put_x(const uint32_t (*y)[4], int st, int seg, int rb, int cg, int lane) {
  uint4* px = &g_xr[2 * st][seg][(rb * 36 + cg * 2) * 32 + lane];
  px[0] = make_uint4(y[0][0], y[0][1], y[0][2], y[0][3]);
  px[32] = make_uint4(y[1][0], y[1][1], y[1][2], y[1][3]);
  float m[2], q[2];
#pragma unroll
  for (int r = 0; r < 2; r++)
    m[r] = ((blo(y[0][r]) + bhi(y[0][r])) + (blo(y[0][r + 2]) + bhi(y[0][r + 2]))) + ((blo(y[1][r]) + bhi(y[1][r])) + (blo(y[1][r + 2]) + bhi(y[1][r + 2])));
#pragma unroll
  for (int o = 1; o < 4; o *= 2) { m[0] += __shfl_xor_sync(~0u, m[0], o); m[1] += __shfl_xor_sync(~0u, m[1], o); }
#pragma unroll
  for (int r = 0; r < 2; r++) {
    m[r] *= (1.f / 32); q[r] = 0.f;
#pragma unroll
    for (int i = 0; i < 4; i++) { const uint32_t v = y[i >> 1][r + (i & 1) * 2]; const float a = blo(v) - m[r], b = bhi(v) - m[r]; q[r] += a * a + b * b; }
  }
#pragma unroll
  for (int o = 1; o < 4; o *= 2) { q[0] += __shfl_xor_sync(~0u, q[0], o); q[1] += __shfl_xor_sync(~0u, q[1], o); }
  if ((lane & 3) == 0) g_stA[st][seg][rb][cg][lane >> 2] = make_float4(m[0], q[0], m[1], q[1]);
}

__device__ __forceinline__ void role_W(uint32_t sb, int c, uint32_t epoch, const bf16* __restrict__ x, const bf16* __restrict__ Wo, bf16* __restrict__ out) {
  const int tid = threadIdx.x, lane = tid & 31, w = __shfl_sync(~0u, (tid >> 5) & 3, 0), wg = __shfl_sync(~0u, tid >> 7, 0);
  const int ks = c / 3, ns = c % 3, k0 = ks * 37;
  if (tid < 192) {
    const int r = tid / 24, nb = tid % 24;
    const bf16* src = Wo + (size_t)(k0 * 16 + r) * 576 + ns * 192 + nb * 8;
    const uint32_t dst = sb + nb * 128 + r * 16;
    const int nblk = min(74, 512 - 2 * k0);
#pragma unroll 4
    for (int b = 0; b < nblk; b++) cp16(dst + b * 3072, src + b * 8 * 576);
    for (int b = nblk; b < 74; b++) sts4(dst + b * 3072, 0, 0, 0, 0);
  }
  asm volatile("cp.async.commit_group;" ::: "memory");
#pragma unroll 1
  for (int u = c * 8 + (tid >> 5); u < NSEG * 18; u += G_W * 8) {
    const int seg = u / 18, rb = (u % 18) / 9, cp = u % 9;
    const uint32_t* p0 = (const uint32_t*)(x + (size_t)(seg * 32 + 2 * (lane >> 2) + rb) * 576) + cp * 32 + (lane & 3);
    uint32_t y[4][4];
#pragma unroll
    for (int i = 0; i < 4; i++) { y[i][0] = __ldg(p0 + i * 8); y[i][2] = __ldg(p0 + i * 8 + 4); y[i][1] = __ldg(p0 + i * 8 + 16 * 288); y[i][3] = __ldg(p0 + i * 8 + 16 * 288 + 4); }
    put_x(&y[0], 0, seg, rb, 2 * cp, lane);
    put_x(&y[2], 0, seg, rb, 2 * cp + 1, lane);
    flag_add(&g_fXA[0][seg][rb][0]);
  }
  asm volatile("cp.async.wait_group 0;" ::: "memory");
  fence_async();
  __syncthreads();
  GT(79, 0);
  const int L = w >> 1, rb = w & 1;
#pragma unroll 1
  for (int s = wg; s < NSTEP; s += 2) {
    const int seg = s - L * LAG;
    const bool on = (uint32_t)seg < (uint32_t)NSEG;
    float acc[96];
    if (on) {
      const int hh = min((k0 >> 3) + min(lane, 5), min((k0 + 36) >> 3, 31));
      uint32_t it = 0;
      while (!__all_sync(~0u, ld_acq(&g_fO[L][seg][hh]) == epoch + 1)) { if (FB > 0) __nanosleep(FB); if (++it > SPIN_MAX) __trap(); }
    }
    GT(s, 0);
    gemm_rs<192, 37>(acc, &g_O[0][0][0][0][0] + (uint32_t)((((L * ORING + (seg & (ORING - 1))) * 2 + rb) * 256 + k0) * 32 + lane), sb, [] {});
    GT(s, 1);
    if (on) {
      const uint32_t tag = PRING == NSEG ? (epoch + 1) & 1 : ((seg / PRING) + 1) & 1;
      uint4* const pp = &g_P[L][seg & (PRING - 1)][0][rb][ns * 12][lane];
#pragma unroll
      for (int i = 0; i < 12; i++)
        st_rlx(pp + ks * 2304 + i * 32, make_uint4((pk(acc[8 * i], acc[8 * i + 1]) & ~1u) | tag, pk(acc[8 * i + 2], acc[8 * i + 3]), pk(acc[8 * i + 4], acc[8 * i + 5]), pk(acc[8 * i + 6], acc[8 * i + 7])));
      if (ks < 6) {
        const int cg = ns * 6 + ks;
        uint32_t v[2][8][4];
        ld_rlx(v[0][7], &g_xr[1 + 2 * L][seg][(rb * 36 + cg * 2) * 32 + lane]);
        ld_rlx(v[1][7], &g_xr[1 + 2 * L][seg][(rb * 36 + cg * 2 + 1) * 32 + lane]);
        __nanosleep(RD);
        uint32_t it = 0;
        while (true) {
          uint32_t bad = 0;
#pragma unroll
          for (int k = 0; k < 7; k++) { ld_rlx(v[0][k], pp + k * 2304 + ks * 64); ld_rlx(v[1][k], pp + k * 2304 + ks * 64 + 32); }
#pragma unroll
          for (int k = 0; k < 7; k++) bad |= (v[0][k][0] ^ tag) | (v[1][k][0] ^ tag);
          if (__all_sync(~0u, (bad & 1) == 0)) break;
          if (++it > SPIN_MAX) __trap();
        }
        GT(s, 2);
        uint32_t y[2][4];
#pragma unroll
        for (int i = 0; i < 2; i++)
#pragma unroll
          for (int r = 0; r < 4; r++) {
            float lo = 0.f, hi = 0.f;
#pragma unroll
            for (int k = 0; k < 8; k++) { lo += blo(v[i][k][r]); hi += bhi(v[i][k][r]); }
            y[i][r] = pk(lo, hi);
          }
        if (L == 0) {
          put_x(y, 1, seg, rb, cg, lane);
          flag_add(&g_fXA[1][seg][rb][0]);
        } else {
          uint32_t* po = (uint32_t*)(out + (size_t)(seg * 32 + 2 * (lane >> 2) + rb) * 576) + cg * 16 + (lane & 3);
#pragma unroll
          for (int i = 0; i < 2; i++) { po[i * 8] = y[i][0]; po[i * 8 + 4] = y[i][2]; po[i * 8 + 16 * 288] = y[i][1]; po[i * 8 + 16 * 288 + 4] = y[i][3]; }
          if (c == 0 && s == NSTEP - 1 && rb == 0 && lane == 0) g_epoch = epoch + 1;
        }
        GT(s, 3);
      }
    }
  }
}

constexpr uint32_t AQ_KV = 193536, AQ_Q = AQ_KV + 4 * 24 * 304;
__device__ __forceinline__ void role_AQ(uint8_t* smraw, uint32_t sb, int c, uint32_t epoch, const bf16* __restrict__ wqkv) {
  const int tid = threadIdx.x, lane = tid & 31, w = __shfl_sync(~0u, (tid >> 5) & 3, 0), wg = __shfl_sync(~0u, tid >> 7, 0);
  if (tid < 252) {
    const int r = tid % 84, part = r / 28, cw = r % 28;
    const bool ok = 2 * cw < min(54, 576 - 54 * c);
    const bf16* src = wqkv + (size_t)(tid / 84) * 8 * 1728 + part * 576 + 54 * c + 2 * cw;
    uint32_t dst = sb + (tid / 84) * 2688 + (part * 7 + (cw >> 2)) * 128 + (cw & 3) * 4;
#pragma unroll 1
    for (int b = 0; b < 24; b++, src += 24 * 1728, dst += 3 * 2688) {
#pragma unroll
      for (int k = 0; k < 8; k++) { if (ok) cp4(dst + k * 16, src + k * 1728); else sts1(dst + k * 16, 0); }
    }
  }
  for (int i = tid; i < (4 * 24 * 304 + 4 * 16 * 144) / 16; i += 256) sts4(sb + AQ_KV + i * 16, 0, 0, 0, 0);
  cp_wait_all();
  fence_async();
  __syncthreads();
  GT(79, 0);
  const int st = w >> 1, rb = w & 1, g = lane >> 2, q = lane & 3;
  const uint32_t kvb = sb + AQ_KV + w * 24 * 304, qb = sb + AQ_Q + w * 16 * 144;
  const uint32_t csa = sb + AQ_KV + 288 + (q >> 1) * 304 + (q & 1) * 8;
  if (wg == 1) {
    if (tid < 128 + 84) {
      const int r = tid - 128;
      float s0 = 0.f, s1 = 0.f;
#pragma unroll 2
      for (int b = 0; b < 72; b++) {
#pragma unroll
        for (int k = 0; k < 8; k++) {
          const uint32_t v = *(const uint32_t*)(smraw + b * 2688 + (r >> 2) * 128 + ((k + (r >> 2)) & 7) * 16 + (r & 3) * 4);
          s0 += blo(v); s1 += bhi(v);
        }
      }
      *(float2*)(smraw + AQ_KV + 288 + (r >> 2) * 608 + ((r >> 1) & 1) * 304 + (r & 1) * 8) = make_float2(s0, s1);
    }
    asm volatile("bar.sync 4, 128;" ::: "memory");
    asm volatile("bar.arrive 5, 256;" ::: "memory");
  }
#pragma unroll 1
  for (int n = wg; n < NSEG + LEAD; n += 2) {
    const int seg = n - st * LEAD;
    const bool on = (uint32_t)seg < (uint32_t)NSEG;
    float acc[84];
    if (on) flag_wait(&g_fXA[st][seg][rb][0], (epoch + 1) * (st ? 18 : 9));
    GT(n, 0);
    float mean0, mean1, rs0, rs1;
    gemm_rs<168, 36>(acc, &g_xr[2 * st][on ? seg : 0][rb * 36 * 32 + lane], sb, [&] {
      uint4 sv[5];
#pragma unroll
      for (int i = 0; i < 5; i++) sv[i] = ld_rlx((const uint4*)&g_stA[st][on ? seg : 0][rb][min(4 * i + q, 17)][g]);
      float t0 = 0.f, t1 = 0.f;
#pragma unroll
      for (int i = 0; i < 5; i++) if (i < 4 || q < 2) { t0 += __uint_as_float(sv[i].x); t1 += __uint_as_float(sv[i].z); }
#pragma unroll
      for (int o = 1; o < 4; o *= 2) { t0 += __shfl_xor_sync(~0u, t0, o); t1 += __shfl_xor_sync(~0u, t1, o); }
      mean0 = t0 * (1.f / 18); mean1 = t1 * (1.f / 18);
      t0 = 0.f; t1 = 0.f;
#pragma unroll
      for (int i = 0; i < 5; i++) if (i < 4 || q < 2) {
        const float d0 = __uint_as_float(sv[i].x) - mean0, d1 = __uint_as_float(sv[i].z) - mean1;
        t0 += __uint_as_float(sv[i].y) + 32.f * d0 * d0; t1 += __uint_as_float(sv[i].w) + 32.f * d1 * d1;
      }
#pragma unroll
      for (int o = 1; o < 4; o *= 2) { t0 += __shfl_xor_sync(~0u, t0, o); t1 += __shfl_xor_sync(~0u, t1, o); }
      rs0 = rsqrtf(t0 * (1.f / 576) + 1e-5f); rs1 = rsqrtf(t1 * (1.f / 576) + 1e-5f);
      if (n > 0) asm volatile("bar.sync %0, 256;" :: "r"(2 + wg) : "memory");
    });
    GT(n, 1);
    if (n == 0) asm volatile("bar.sync 5, 256;" ::: "memory");
    uint32_t ow[3][3][2];
    if (on) {
      const uint32_t pos0 = (2 * n) % 3, pos1 = (2 * n + 1) % 3, pos2 = (2 * n + 2) % 3;
      float cs_[21][2];
#pragma unroll
      for (int jn = 0; jn < 21; jn++) asm volatile("ld.shared.v2.f32 {%0,%1}, [%2];" : "=f"(cs_[jn][0]), "=f"(cs_[jn][1]) : "r"(csa + jn * 608));
#pragma unroll
      for (int jn = 0; jn < 21; jn++) {
        const int part = jn / 7, cc = 8 * (jn % 7) + 2 * q;
        const uint32_t co = 2 * cc + 12 * ((cc >= 18) + (cc >= 36));
        const uint32_t lo = part == 0 ? qb + g * 144 + co : kvb + (pos1 * 8 + g) * 304 + (part - 1) * 144 + co;
        const uint32_t hi = part == 0 ? lo + 8 * 144 : kvb + (pos2 * 8 + g) * 304 + (part - 1) * 144 + co;
        const float c0 = cs_[jn][0], c1 = cs_[jn][1];
        if (cc < 54) {
          sts1(lo, pk(fmaf(-mean0, c0, acc[4 * jn]) * rs0, fmaf(-mean0, c1, acc[4 * jn + 1]) * rs0));
          sts1(hi, pk(fmaf(-mean1, c0, acc[4 * jn + 2]) * rs1, fmaf(-mean1, c1, acc[4 * jn + 3]) * rs1));
        }
      }
      __syncwarp();
      const uint32_t ka = kvb + (lane & 7) * 304 + min(lane >> 3, 2) * 16;
      const float cs = 0.23570226039551584f * 1.4426950408889634f;
#pragma unroll
      for (int lh = 0; lh < 3; lh++) {
        uint32_t qa[4], qc[2], kf[3][4], vf[3][4];
        ldsm4(qa, qb + (lane & 15) * 144 + (lane >> 4) * 16 + lh * 48);
        ldsm2(qc, qb + (lane & 15) * 144 + 32 + lh * 48);
        ldsm4(kf[0], ka + pos0 * 2432 + lh * 48); ldsm4(kf[1], ka + pos1 * 2432 + lh * 48); ldsm4(kf[2], ka + pos2 * 2432 + lh * 48);
        ldsm4t(vf[0], ka + pos0 * 2432 + 144 + lh * 48); ldsm4t(vf[1], ka + pos1 * 2432 + 144 + lh * 48); ldsm4t(vf[2], ka + pos2 * 2432 + 144 + lh * 48);
        float sc[3][4];
#pragma unroll
        for (int b = 0; b < 3; b++) {
          sc[b][0] = sc[b][1] = sc[b][2] = sc[b][3] = 0.f;
          HMMA(sc[b], qa[0], qa[1], qa[2], qa[3], kf[b][0], kf[b][1]);
          HMMA8(sc[b], qc[0], qc[1], kf[b][2]);
        }
        const bool e0 = 2 * q <= g, e1 = 2 * q + 1 <= g;
        float a0 = e0 ? sc[1][0] : (seg > 0 ? sc[0][0] : -INFINITY), a1 = e1 ? sc[1][1] : (seg > 0 ? sc[0][1] : -INFINITY);
        float b0 = e0 ? sc[2][2] : sc[1][2], b1 = e1 ? sc[2][3] : sc[1][3];
        float m0 = fmaxf(a0, a1), m1 = fmaxf(b0, b1);
        m0 = fmaxf(m0, __shfl_xor_sync(~0u, m0, 1)); m1 = fmaxf(m1, __shfl_xor_sync(~0u, m1, 1));
        m0 = fmaxf(m0, __shfl_xor_sync(~0u, m0, 2)); m1 = fmaxf(m1, __shfl_xor_sync(~0u, m1, 2));
        a0 = ex2((a0 - m0) * cs); a1 = ex2((a1 - m0) * cs); b0 = ex2((b0 - m1) * cs); b1 = ex2((b1 - m1) * cs);
        float s0 = a0 + a1, s1 = b0 + b1;
        s0 += __shfl_xor_sync(~0u, s0, 1); s1 += __shfl_xor_sync(~0u, s1, 1);
        s0 += __shfl_xor_sync(~0u, s0, 2); s1 += __shfl_xor_sync(~0u, s1, 2);
        s0 = rcp(s0); s1 = rcp(s1);
        a0 *= s0; a1 *= s0; b0 *= s1; b1 *= s1;
        const uint32_t p00 = pk(e0 ? 0.f : a0, e1 ? 0.f : a1), p01 = pk(e0 ? a0 : 0.f, e1 ? a1 : 0.f);
        const uint32_t p11 = pk(e0 ? 0.f : b0, e1 ? 0.f : b1), p12 = pk(e0 ? b0 : 0.f, e1 ? b1 : 0.f);
#pragma unroll
        for (int cb = 0; cb < 3; cb++) {
          float o[4] = {0.f, 0.f, 0.f, 0.f};
          HMMA(o, p00, 0u, p01, p11, vf[0][cb], vf[1][cb]);
          HMMA8(o, 0u, p12, vf[2][cb]);
          ow[lh][cb][0] = pk(o[0], o[1]); ow[lh][cb][1] = pk(o[2], o[3]);
        }
      }
    }
    asm volatile("bar.arrive %0, 256;" :: "r"(3 - wg) : "memory");
    if (on) {
      uint2* po = (uint2*)&g_oA[st][seg][rb * 36 * 32 + g * 4];
#pragma unroll
      for (int lh = 0; lh < 3; lh++)
#pragma unroll
        for (int cb = 0; cb < 3; cb++) {
          const int col = 54 * c + 18 * lh + 8 * cb + 2 * q;
          if ((cb < 2 || q == 0) && col < 576) po[(col >> 4) * 64 + (col & 6) + ((col >> 3) & 1)] = make_uint2(ow[lh][cb][0], ow[lh][cb][1]);
        }
      flag_add(&g_fOA[st][seg][rb][0]);
    }
    GT(n, 2);
  }
  if (wg == ((NSEG + LEAD) & 1)) asm volatile("bar.sync %0, 256;" :: "r"(2 + wg) : "memory");
}

__device__ __forceinline__ void role_AO(uint8_t* smraw, uint32_t sb, int c, uint32_t epoch, const bf16* __restrict__ wo) {
  const int tid = threadIdx.x, lane = tid & 31, w = __shfl_sync(~0u, (tid >> 5) & 3, 0), wg = __shfl_sync(~0u, tid >> 7, 0);
  if (tid < 144) {
    const int r = tid / 18, nb = tid % 18;
#pragma unroll 4
    for (int b = 0; b < 72; b++) cp16(sb + b * 2304 + nb * 128 + r * 16, wo + (size_t)(b * 8 + r) * 576 + c * 144 + nb * 8);
  }
  cp_wait_all();
  fence_async();
  __syncthreads();
  GT(79, 0);
  const int st = w >> 1, rb = w & 1, g = lane >> 2, q = lane & 3;
  const uint32_t tag = (epoch + 1) & 1;
#pragma unroll 1
  for (int n = wg; n < NSEG + LEAD; n += 2) {
    const int seg = n - st * LEAD;
    const bool on = (uint32_t)seg < (uint32_t)NSEG;
    float acc[72];
    uint32_t res[9][4];
    const int o = (rb * 36 + c * 9) * 32 + lane;
    if (on) flag_wait(&g_fXA[st][seg][rb][0], (epoch + 1) * (st ? 18 : 9));
#pragma unroll
    for (int i = 0; i < 9; i++) ld_rlx(res[i], &g_xr[2 * st][on ? seg : 0][o] + i * 32);
    if (on) flag_wait(&g_fOA[st][seg][rb][0], (epoch + 1) * G_AQ);
    GT(n, 0);
    gemm_rs<144, 36>(acc, &g_oA[st][on ? seg : 0][rb * 36 * 32 + lane], sb, [] {});
    GT(n, 1);
    if (on) {
      float s0 = 0.f, s1 = 0.f;
#pragma unroll
      for (int i = 0; i < 36; i++) {
        const uint32_t y = pk(acc[2 * i] + blo(res[i >> 2][i & 3]), acc[2 * i + 1] + bhi(res[i >> 2][i & 3]));
        res[i >> 2][i & 3] = y;
        acc[2 * i] = blo(y); acc[2 * i + 1] = bhi(y);
        if (i & 1) s1 += acc[2 * i] + acc[2 * i + 1]; else s0 += acc[2 * i] + acc[2 * i + 1];
      }
      s0 += __shfl_xor_sync(~0u, s0, 1); s1 += __shfl_xor_sync(~0u, s1, 1);
      s0 += __shfl_xor_sync(~0u, s0, 2); s1 += __shfl_xor_sync(~0u, s1, 2);
      float m0 = s0 * (1.f / 144), m1 = s1 * (1.f / 144), q0 = 0.f, q1 = 0.f;
#pragma unroll
      for (int i = 0; i < 36; i++) {
        const float mm = (i & 1) ? m1 : m0, d0 = acc[2 * i] - mm, d1 = acc[2 * i + 1] - mm;
        if (i & 1) q1 += d0 * d0 + d1 * d1; else q0 += d0 * d0 + d1 * d1;
      }
      q0 += __shfl_xor_sync(~0u, q0, 1); q1 += __shfl_xor_sync(~0u, q1, 1);
      q0 += __shfl_xor_sync(~0u, q0, 2); q1 += __shfl_xor_sync(~0u, q1, 2);
      if (q == 0) st_rlx(&g_stat[st][seg][rb][c * 8 + g], make_uint4(__float_as_uint(m0), (__float_as_uint(q0) & ~1u) | tag, __float_as_uint(m1), __float_as_uint(q1)));
#pragma unroll
      for (int i = 0; i < 9; i++) g_xr[1 + 2 * st][seg][o + i * 32] = make_uint4(res[i][0], res[i][1], res[i][2], res[i][3]);
      uint4 sv;
      {
        uint32_t it = 0;
        do { sv = ld_rlx(&g_stat[st][seg][rb][q * 8 + g]); if (++it > SPIN_MAX) __trap(); } while (!__all_sync(~0u, (sv.y & 1) == tag));
      }
      m0 = __uint_as_float(sv.x); m1 = __uint_as_float(sv.z);
      float t0 = m0 + __shfl_xor_sync(~0u, m0, 1), t1 = m1 + __shfl_xor_sync(~0u, m1, 1);
      t0 += __shfl_xor_sync(~0u, t0, 2); t1 += __shfl_xor_sync(~0u, t1, 2);
      t0 *= 0.25f; t1 *= 0.25f;
      q0 = __uint_as_float(sv.y) + 144.f * (m0 - t0) * (m0 - t0); q1 = __uint_as_float(sv.w) + 144.f * (m1 - t1) * (m1 - t1);
      q0 += __shfl_xor_sync(~0u, q0, 1); q1 += __shfl_xor_sync(~0u, q1, 1);
      q0 += __shfl_xor_sync(~0u, q0, 2); q1 += __shfl_xor_sync(~0u, q1, 2);
      const float r0 = rsqrtf(q0 * (1.f / 576) + 1e-5f), r1 = rsqrtf(q1 * (1.f / 576) + 1e-5f);
      uint32_t* px = (uint32_t*)&g_xnB[st][seg][0] + (rb * 144 + c * 18) * 32 + lane;
#pragma unroll
      for (int jn = 0; jn < 18; jn++) {
        px[jn * 32] = pk((acc[4 * jn] - t0) * r0, (acc[4 * jn + 1] - t0) * r0);
        px[jn * 32 + 2304] = pk((acc[4 * jn + 2] - t1) * r1, (acc[4 * jn + 3] - t1) * r1);
      }
      flag_add(&g_fXB[st][seg][0]);
    }
    GT(n, 2);
  }
}

__global__ void __launch_bounds__(256, 1)
g_kernel(const bf16* __restrict__ x, const bf16* __restrict__ wqkv, const bf16* __restrict__ wo, const bf16* __restrict__ Wo, bf16* __restrict__ out) {
  extern __shared__ __align__(1024) uint8_t smraw[];
  const uint32_t sb = smem_u32(smraw);
  const uint32_t epoch = *(volatile uint32_t*)&g_epoch;
  const int b = blockIdx.x;
  GT(79, 1);
  if (b < G_W) role_W(sb, b, epoch, x, Wo, out);
  else if (b < G_W + G_AQ) role_AQ(smraw, sb, b - G_W, epoch, wqkv);
  else role_AO(smraw, sb, b - G_W - G_AQ, epoch, wo);
}

extern "C" void kernel_launch(void* const* d_in, const int* in_sizes, int n_in, void* d_out, int out_size) {
  const bf16 *x = (const bf16*)d_in[0], *wqkv = (const bf16*)d_in[1], *wo = (const bf16*)d_in[2], *mem0 = (const bf16*)d_in[4];
  const bf16 *Wq = (const bf16*)d_in[5], *Wk = (const bf16*)d_in[6], *Wv = (const bf16*)d_in[7], *Wo = (const bf16*)d_in[8];
  cudaFuncSetAttribute(h_kernel, cudaFuncAttributeMaxDynamicSharedMemorySize, H_SMEM);
  cudaFuncSetAttribute(g_kernel, cudaFuncAttributeMaxDynamicSharedMemorySize, G_SMEM);
  cudaStream_t st = cudaStreamPerThread;
  h_kernel<<<96, 512, H_SMEM, st>>>(Wq, Wk, Wv, Wo, mem0, x, wqkv, wo);
  cudaLaunchConfig_t cfg = {};
  cfg.gridDim = dim3(G_W + G_AQ + G_AO); cfg.blockDim = dim3(256); cfg.dynamicSmemBytes = G_SMEM; cfg.stream = st;
  cudaLaunchAttribute at[1];
  at[0].id = cudaLaunchAttributeProgrammaticStreamSerialization; at[0].val.programmaticStreamSerializationAllowed = 1;
  cfg.attrs = at; cfg.numAttrs = 1;
  cudaLaunchKernelEx(&cfg, g_kernel, x, wqkv, wo, Wo, (bf16*)d_out);
}
```

```cpp
#include <cuda_runtime.h>
#include <cuda_bf16.h>
#include <stdint.h>
typedef __nv_bfloat16 bf16;

#define LAG 7
#define EX 2
#define N2 0
#ifndef NV
#define NV 20
#endif
#define PD 900
#define OD 1000
#define FM 3
#define PSD 300
#define FB 50
#define PDS 150
#define PDJ 0
#define N1 4
#define NS 0
#define WD 8000
#define HP 3
#define AQF 100
#define GQ 2
#define KRV 35
#define RPF 2
#define OW 1
#define VW 1
constexpr int NSEG = 64;
constexpr int NSTEP = NSEG + LAG;
constexpr int LEAD = LAG + 2;
constexpr int ORING = 16, PRING = 16;

__device__ uint4 g_xa[2][NSEG][2304];
__device__ uint4 g_stA[2][NSEG][2][18][8];
__device__ uint4 g_oA[2][NSEG][2304];
__device__ uint4 g_xb[2][NSEG][2304];
__device__ float2 g_stB[2][NSEG][4][32];
__device__ uint4 g_O[3][ORING][2][256][32];
__device__ uint4 g_P[2][PRING][7][2][36][32];
__device__ uint4 g_ones[1152];
__device__ uint4 g_acc[4][1536];
__device__ uint32_t g_fXA[2][NSEG][2][8], g_fP[2][NSEG][2][3][8], g_fOA[2][NSEG][2][8], g_fXB[2][NSEG][8];
__device__ uint32_t g_fO[2][NSEG][32];
__device__ uint32_t g_epoch;
#define TR(i)
#define TRW(i, ww)
#define GT(n, i)
#define GTR(n, i)
#define REDO(i)

#define OPAQUE(x) asm volatile("" : "+r"(x))
template<int N> __device__ __forceinline__ void pin(float* a) {
#pragma unroll
  for (int i = 0; i < N; i++) asm volatile("" : "+f"(a[i]) :: "memory");
}
__device__ __forceinline__ int lane_id() { int l; asm volatile("mov.u32 %0, %%laneid;" : "=r"(l)); return l; }
constexpr uint32_t SPIN_MAX = 4000000;
__device__ __forceinline__ uint32_t smem_u32(const void* p) { return (uint32_t)__cvta_generic_to_shared(p); }
__device__ __forceinline__ void mbar_init(uint32_t mb, uint32_t n) { asm volatile("mbarrier.init.shared::cta.b64 [%0], %1;" :: "r"(mb), "r"(n) : "memory"); }
__device__ __forceinline__ void mbar_expect(uint32_t mb, uint32_t bytes) { asm volatile("mbarrier.arrive.expect_tx.shared::cta.b64 _, [%0], %1;" :: "r"(mb), "r"(bytes) : "memory"); }
__device__ __forceinline__ void mbar_arrive(uint32_t mb) { asm volatile("mbarrier.arrive.shared::cta.b64 _, [%0];" :: "r"(mb) : "memory"); }
__device__ __forceinline__ void mbar_wait(uint32_t mb, uint32_t par) {
  asm volatile("{.reg .pred p; .reg .u32 c;\n"
               "mbarrier.try_wait.parity.shared::cta.b64 p, [%0], %1; @p bra.uni D_%=; mov.u32 c, 0;\n"
               "W_%=: mbarrier.try_wait.parity.shared::cta.b64 p, [%0], %1; @p bra.uni D_%=;\n"
               "add.u32 c, c, 1; setp.lt.u32 p, c, 4000000; @p bra.uni W_%=; trap;\n"
               "D_%=: }" :: "r"(mb), "r"(par) : "memory");
}
__device__ __forceinline__ void st_async1(uint32_t a, uint32_t v, uint32_t mb) {
  asm volatile("st.async.weak.shared::cluster.mbarrier::complete_tx::bytes.b32 [%0], %1, [%2];" :: "r"(a), "r"(v), "r"(mb) : "memory");
}
__device__ __forceinline__ void st_async4(uint32_t a, uint32_t x, uint32_t y, uint32_t z, uint32_t w, uint32_t mb) {
  asm volatile("st.async.weak.shared::cluster.mbarrier::complete_tx::bytes.v4.b32 [%0], {%1,%2,%3,%4}, [%5];" :: "r"(a), "r"(x), "r"(y), "r"(z), "r"(w), "r"(mb) : "memory");
}
__device__ __forceinline__ void fence_async() { asm volatile("fence.proxy.async.shared::cta;" ::: "memory"); }
__device__ __forceinline__ uint32_t drain(uint32_t zero_addr) {
  uint32_t x;
  asm volatile("ld.volatile.shared.b32 %0, [%1];" : "=r"(x) : "r"(zero_addr) : "memory");
  return x;
}
__device__ __forceinline__ void arrive_after(uint32_t mb, uint32_t x, int lane) {
  asm volatile("{.reg .pred p; setp.eq.u32 p, %1, %2; @p mbarrier.arrive.shared::cta.b64 _, [%0];}" :: "r"(mb), "r"(x), "r"(lane) : "memory");
}
__device__ __forceinline__ void publish(uint32_t mb, uint32_t zero_addr, int lane) { arrive_after(mb, drain(zero_addr), lane); }
__device__ __forceinline__ float4 lds_f4(uint32_t a) {
  float4 v; asm volatile("ld.shared.v4.f32 {%0,%1,%2,%3}, [%4];" : "=f"(v.x), "=f"(v.y), "=f"(v.z), "=f"(v.w) : "r"(a)); return v;
}
__device__ __forceinline__ void fence_gpu() { asm volatile("fence.acq_rel.gpu;" ::: "memory"); }
__device__ __forceinline__ void wg_fence() { asm volatile("wgmma.fence.sync.aligned;" ::: "memory"); }
__device__ __forceinline__ void wg_commit() { asm volatile("wgmma.commit_group.sync.aligned;" ::: "memory"); }
template<int N> __device__ __forceinline__ void wg_wait() { asm volatile("wgmma.wait_group.sync.aligned %0;" :: "n"(N) : "memory"); }
__device__ __forceinline__ uint32_t pk(float a, float b) { uint32_t r; asm("cvt.rn.bf16x2.f32 %0, %1, %2;" : "=r"(r) : "f"(b), "f"(a)); return r; }
__device__ __forceinline__ uint32_t pk_tag(float a, float b, uint32_t tag) {
  const uint32_t r = __float_as_uint(a) >> 16;
  return __byte_perm(r + ((r ^ tag) & 1), pk(a, b), 0x7610);
}
__device__ __forceinline__ float blo(uint32_t v) { return __uint_as_float(v << 16); }
__device__ __forceinline__ float bhi(uint32_t v) { return __uint_as_float(v & 0xFFFF0000u); }
__device__ __forceinline__ float ex2(float x) { float y; asm("ex2.approx.ftz.f32 %0, %1;" : "=f"(y) : "f"(x)); return y; }
__device__ __forceinline__ float rcp(float x) { float y; asm("rcp.approx.ftz.f32 %0, %1;" : "=f"(y) : "f"(x)); return y; }
__device__ __forceinline__ uint64_t mkdesc(uint32_t addr, uint32_t lbo, uint32_t sbo) {
  return (uint64_t)((addr & 0x3FFFF) >> 4) | ((uint64_t)(lbo >> 4) << 16) | ((uint64_t)(sbo >> 4) << 32);
}
__device__ __forceinline__ void cp16(uint32_t dst, const void* src) { asm volatile("cp.async.cg.shared.global [%0], [%1], 16;" :: "r"(dst), "l"(src) : "memory"); }
__device__ __forceinline__ void cp4(uint32_t dst, const void* src) { asm volatile("cp.async.ca.shared.global [%0], [%1], 4;" :: "r"(dst), "l"(src) : "memory"); }
__device__ __forceinline__ void cp_wait_all() { asm volatile("cp.async.commit_group; cp.async.wait_group 0;" ::: "memory"); }
__device__ __forceinline__ void ldsm4(uint32_t* r, uint32_t addr) {
  asm volatile("ldmatrix.sync.aligned.m8n8.x4.shared.b16 {%0,%1,%2,%3}, [%4];" : "=r"(r[0]), "=r"(r[1]), "=r"(r[2]), "=r"(r[3]) : "r"(addr) : "memory");
}
__device__ __forceinline__ void ldsm2(uint32_t* r, uint32_t addr) {
  asm volatile("ldmatrix.sync.aligned.m8n8.x2.shared.b16 {%0,%1}, [%2];" : "=r"(r[0]), "=r"(r[1]) : "r"(addr) : "memory");
}
__device__ __forceinline__ void ldsm4t(uint32_t* r, uint32_t addr) {
  asm volatile("ldmatrix.sync.aligned.m8n8.x4.trans.shared.b16 {%0,%1,%2,%3}, [%4];" : "=r"(r[0]), "=r"(r[1]), "=r"(r[2]), "=r"(r[3]) : "r"(addr) : "memory");
}
__device__ __forceinline__ void bulk_g2s(uint32_t dst, const void* src, uint32_t bytes, uint32_t mb) {
  asm volatile("cp.async.bulk.shared::cluster.global.mbarrier::complete_tx::bytes [%0], [%1], %2, [%3];" :: "r"(dst), "l"(src), "r"(bytes), "r"(mb) : "memory");
}
__device__ __forceinline__ void bulk_s2g(void* dst, uint32_t src, uint32_t bytes) {
  asm volatile("cp.async.bulk.global.shared::cta.bulk_group [%0], [%1], %2; cp.async.bulk.commit_group;" :: "l"(dst), "r"(src), "r"(bytes) : "memory");
}
__device__ __forceinline__ void bulk_s2s(uint32_t dst, uint32_t src, uint32_t mb) {
  asm volatile("cp.async.bulk.shared::cluster.shared::cta.mbarrier::complete_tx::bytes [%0], [%1], 8192, [%2];" :: "r"(dst), "r"(src), "r"(mb) : "memory");
}
__device__ __forceinline__ void l2_prefetch(const void* p, uint32_t bytes) { asm volatile("cp.async.bulk.prefetch.L2.global [%0], %1;" :: "l"(p), "r"(bytes) : "memory"); }
__device__ __forceinline__ uint32_t ld_acq(const uint32_t* p) { uint32_t v; asm volatile("ld.acquire.gpu.global.u32 %0, [%1];" : "=r"(v) : "l"(p) : "memory"); return v; }
__device__ __forceinline__ uint4 ld_rlx(const uint4* p) {
  uint4 v; asm volatile("ld.relaxed.gpu.global.v4.b32 {%0,%1,%2,%3}, [%4];" : "=r"(v.x), "=r"(v.y), "=r"(v.z), "=r"(v.w) : "l"(p) : "memory"); return v;
}
__device__ __forceinline__ void ld_rlx(uint32_t* r, const uint4* p) {
  asm volatile("ld.relaxed.gpu.global.v4.b32 {%0,%1,%2,%3}, [%4];" : "=r"(r[0]), "=r"(r[1]), "=r"(r[2]), "=r"(r[3]) : "l"(p) : "memory");
}
__device__ __forceinline__ void st_rlx(uint4* p, uint4 v) {
  asm volatile("st.relaxed.gpu.global.v4.b32 [%0], {%1,%2,%3,%4};" :: "l"(p), "r"(v.x), "r"(v.y), "r"(v.z), "r"(v.w) : "memory");
}
__device__ __forceinline__ void red4(uint4* p, uint32_t a, uint32_t b, uint32_t c, bool on) {
  asm volatile("{.reg .pred p; setp.ne.u32 p, %5, 0; @p red.relaxed.gpu.global.add.noftz.v4.bf16x2 [%0], {%1,%2,%3,%4};}"
               :: "l"(p), "r"(a), "r"(b), "r"(c), "r"(0x3F80u), "r"((uint32_t)on) : "memory");
}
__device__ __forceinline__ void stsm4(uint32_t a, uint32_t x, uint32_t y, uint32_t z, uint32_t w) {
  asm volatile("stmatrix.sync.aligned.m8n8.x4.shared.b16 [%0], {%1,%2,%3,%4};" :: "r"(a), "r"(x), "r"(y), "r"(z), "r"(w) : "memory");
}
__device__ __forceinline__ uint32_t movt(uint32_t v) { uint32_t r; asm volatile("movmatrix.sync.aligned.m8n8.trans.b16 %0, %1;" : "=r"(r) : "r"(v)); return r; }
__device__ __forceinline__ void sts1(uint32_t a, uint32_t v) { asm volatile("st.shared.b32 [%0], %1;" :: "r"(a), "r"(v) : "memory"); }
__device__ __forceinline__ void sts4(uint32_t a, uint32_t x, uint32_t y, uint32_t z, uint32_t w) { asm volatile("st.shared.v4.b32 [%0], {%1,%2,%3,%4};" :: "r"(a), "r"(x), "r"(y), "r"(z), "r"(w) : "memory"); }
__device__ __forceinline__ void flag_wait(const uint32_t* p, uint32_t target) {
  uint32_t it = 0;
  while (ld_acq(p) != target) {
    uint32_t v;
    do { if (FB > 0) __nanosleep(FB); asm volatile("ld.relaxed.gpu.global.u32 %0, [%1];" : "=r"(v) : "l"(p) : "memory"); if (++it > SPIN_MAX) __trap(); } while (v != target);
    fence_gpu();
    break;
  }
}
__device__ __forceinline__ void hint_add(uint32_t* p, int lane) {
  asm volatile("{.reg .pred p; setp.eq.u32 p, %1, 0; @p red.relaxed.gpu.global.inc.u32 [%0], 0xFFFFFFFF;}" :: "l"(p), "r"(lane) : "memory");
}
__device__ __forceinline__ void hint_wait(const uint32_t* p, uint32_t target) {
  uint32_t it = 0, v;
  do { asm volatile("ld.relaxed.gpu.global.u32 %0, [%1];" : "=r"(v) : "l"(p) : "memory"); if (FB > 0 && v != target) __nanosleep(FB); if (++it > SPIN_MAX) __trap(); } while (!__all_sync(~0u, v == target));
}
__device__ __forceinline__ void flag_add(uint32_t* p, int lane) {
  fence_gpu();
  __syncwarp();
  hint_add(p, lane);
}
#define HMMA(d, a0, a1, a2, a3, b0, b1) asm volatile("mma.sync.aligned.m16n8k16.row.col.f32.bf16.bf16.f32 {%0,%1,%2,%3},{%4,%5,%6,%7},{%8,%9},{%0,%1,%2,%3};" \
  : "+f"((d)[0]), "+f"((d)[1]), "+f"((d)[2]), "+f"((d)[3]) : "r"(a0), "r"(a1), "r"(a2), "r"(a3), "r"(b0), "r"(b1))
#define HMMA8(d, a0, a1, b0) asm volatile("mma.sync.aligned.m16n8k8.row.col.f32.bf16.bf16.f32 {%0,%1,%2,%3},{%4,%5},{%6},{%0,%1,%2,%3};" \
  : "+f"((d)[0]), "+f"((d)[1]), "+f"((d)[2]), "+f"((d)[3]) : "r"(a0), "r"(a1), "r"(b0))

template<int ACC> __device__ __forceinline__ void rs24(float* d, const uint32_t* a, uint64_t b) {
  if (ACC) asm volatile("wgmma.mma_async.sync.aligned.m64n24k16.f32.bf16.bf16 {%0,%1,%2,%3,%4,%5,%6,%7,%8,%9,%10,%11},{%12,%13,%14,%15},%16,1,1,1,0;"
    : "+f"(d[0]), "+f"(d[1]), "+f"(d[2]), "+f"(d[3]), "+f"(d[4]), "+f"(d[5]), "+f"(d[6]), "+f"(d[7]), "+f"(d[8]), "+f"(d[9]), "+f"(d[10]), "+f"(d[11])
    : "r"(a[0]), "r"(a[1]), "r"(a[2]), "r"(a[3]), "l"(b));
  else asm volatile("wgmma.mma_async.sync.aligned.m64n24k16.f32.bf16.bf16 {%0,%1,%2,%3,%4,%5,%6,%7,%8,%9,%10,%11},{%12,%13,%14,%15},%16,0,1,1,0;"
    : "=f"(d[0]), "=f"(d[1]), "=f"(d[2]), "=f"(d[3]), "=f"(d[4]), "=f"(d[5]), "=f"(d[6]), "=f"(d[7]), "=f"(d[8]), "=f"(d[9]), "=f"(d[10]), "=f"(d[11])
    : "r"(a[0]), "r"(a[1]), "r"(a[2]), "r"(a[3]), "l"(b));
}

template<int ACC> __device__ __forceinline__ void rs32(float* d, const uint32_t* a, uint64_t b) {
  if (ACC) asm volatile("wgmma.mma_async.sync.aligned.m64n32k16.f32.bf16.bf16 {%0,%1,%2,%3,%4,%5,%6,%7,%8,%9,%10,%11,%12,%13,%14,%15},{%16,%17,%18,%19},%20,1,1,1,0;"
    : "+f"(d[0]), "+f"(d[1]), "+f"(d[2]), "+f"(d[3]), "+f"(d[4]), "+f"(d[5]), "+f"(d[6]), "+f"(d[7]), "+f"(d[8]), "+f"(d[9]), "+f"(d[10]), "+f"(d[11]),
      "+f"(d[12]), "+f"(d[13]), "+f"(d[14]), "+f"(d[15])
    : "r"(a[0]), "r"(a[1]), "r"(a[2]), "r"(a[3]), "l"(b));
  else asm volatile("wgmma.mma_async.sync.aligned.m64n32k16.f32.bf16.bf16 {%0,%1,%2,%3,%4,%5,%6,%7,%8,%9,%10,%11,%12,%13,%14,%15},{%16,%17,%18,%19},%20,0,1,1,0;"
    : "=f"(d[0]), "=f"(d[1]), "=f"(d[2]), "=f"(d[3]), "=f"(d[4]), "=f"(d[5]), "=f"(d[6]), "=f"(d[7]), "=f"(d[8]), "=f"(d[9]), "=f"(d[10]), "=f"(d[11]),
      "=f"(d[12]), "=f"(d[13]), "=f"(d[14]), "=f"(d[15])
    : "r"(a[0]), "r"(a[1]), "r"(a[2]), "r"(a[3]), "l"(b));
}

template<int ACC> __device__ __forceinline__ void rs48(float* d, const uint32_t* a, uint64_t b) {
  if (ACC) asm volatile("wgmma.mma_async.sync.aligned.m64n48k16.f32.bf16.bf16 {%0,%1,%2,%3,%4,%5,%6,%7,%8,%9,%10,%11,%12,%13,%14,%15,%16,%17,%18,%19,%20,%21,%22,%23},{%24,%25,%26,%27},%28,1,1,1,0;"
    : "+f"(d[0]), "+f"(d[1]), "+f"(d[2]), "+f"(d[3]), "+f"(d[4]), "+f"(d[5]), "+f"(d[6]), "+f"(d[7]), "+f"(d[8]), "+f"(d[9]), "+f"(d[10]), "+f"(d[11]),
      "+f"(d[12]), "+f"(d[13]), "+f"(d[14]), "+f"(d[15]), "+f"(d[16]), "+f"(d[17]), "+f"(d[18]), "+f"(d[19]), "+f"(d[20]), "+f"(d[21]), "+f"(d[22]), "+f"(d[23])
    : "r"(a[0]), "r"(a[1]), "r"(a[2]), "r"(a[3]), "l"(b));
  else asm volatile("wgmma.mma_async.sync.aligned.m64n48k16.f32.bf16.bf16 {%0,%1,%2,%3,%4,%5,%6,%7,%8,%9,%10,%11,%12,%13,%14,%15,%16,%17,%18,%19,%20,%21,%22,%23},{%24,%25,%26,%27},%28,0,1,1,0;"
    : "=f"(d[0]), "=f"(d[1]), "=f"(d[2]), "=f"(d[3]), "=f"(d[4]), "=f"(d[5]), "=f"(d[6]), "=f"(d[7]), "=f"(d[8]), "=f"(d[9]), "=f"(d[10]), "=f"(d[11]),
      "=f"(d[12]), "=f"(d[13]), "=f"(d[14]), "=f"(d[15]), "=f"(d[16]), "=f"(d[17]), "=f"(d[18]), "=f"(d[19]), "=f"(d[20]), "=f"(d[21]), "=f"(d[22]), "=f"(d[23])
    : "r"(a[0]), "r"(a[1]), "r"(a[2]), "r"(a[3]), "l"(b));
}

template<int ACC> __device__ __forceinline__ void rs56(float* d, const uint32_t* a, uint64_t b) {
  if (ACC) asm volatile("wgmma.mma_async.sync.aligned.m64n56k16.f32.bf16.bf16 {%0,%1,%2,%3,%4,%5,%6,%7,%8,%9,%10,%11,%12,%13,%14,%15,%16,%17,%18,%19,%20,%21,%22,%23,%24,%25,%26,%27},{%28,%29,%30,%31},%32,1,1,1,0;"
    : "+f"(d[0]), "+f"(d[1]), "+f"(d[2]), "+f"(d[3]), "+f"(d[4]), "+f"(d[5]), "+f"(d[6]), "+f"(d[7]), "+f"(d[8]), "+f"(d[9]), "+f"(d[10]), "+f"(d[11]),
      "+f"(d[12]), "+f"(d[13]), "+f"(d[14]), "+f"(d[15]), "+f"(d[16]), "+f"(d[17]), "+f"(d[18]), "+f"(d[19]), "+f"(d[20]), "+f"(d[21]), "+f"(d[22]), "+f"(d[23]),
      "+f"(d[24]), "+f"(d[25]), "+f"(d[26]), "+f"(d[27])
    : "r"(a[0]), "r"(a[1]), "r"(a[2]), "r"(a[3]), "l"(b));
  else asm volatile("wgmma.mma_async.sync.aligned.m64n56k16.f32.bf16.bf16 {%0,%1,%2,%3,%4,%5,%6,%7,%8,%9,%10,%11,%12,%13,%14,%15,%16,%17,%18,%19,%20,%21,%22,%23,%24,%25,%26,%27},{%28,%29,%30,%31},%32,0,1,1,0;"
    : "=f"(d[0]), "=f"(d[1]), "=f"(d[2]), "=f"(d[3]), "=f"(d[4]), "=f"(d[5]), "=f"(d[6]), "=f"(d[7]), "=f"(d[8]), "=f"(d[9]), "=f"(d[10]), "=f"(d[11]),
      "=f"(d[12]), "=f"(d[13]), "=f"(d[14]), "=f"(d[15]), "=f"(d[16]), "=f"(d[17]), "=f"(d[18]), "=f"(d[19]), "=f"(d[20]), "=f"(d[21]), "=f"(d[22]), "=f"(d[23]),
      "=f"(d[24]), "=f"(d[25]), "=f"(d[26]), "=f"(d[27])
    : "r"(a[0]), "r"(a[1]), "r"(a[2]), "r"(a[3]), "l"(b));
}

template<int ACC> __device__ __forceinline__ void rs64(float* d, const uint32_t* a, uint64_t b) {
  if (ACC) asm volatile("wgmma.mma_async.sync.aligned.m64n64k16.f32.bf16.bf16 {%0,%1,%2,%3,%4,%5,%6,%7,%8,%9,%10,%11,%12,%13,%14,%15,%16,%17,%18,%19,%20,%21,%22,%23,%24,%25,%26,%27,%28,%29,%30,%31},{%32,%33,%34,%35},%36,1,1,1,0;"
    : "+f"(d[0]), "+f"(d[1]), "+f"(d[2]), "+f"(d[3]), "+f"(d[4]), "+f"(d[5]), "+f"(d[6]), "+f"(d[7]), "+f"(d[8]), "+f"(d[9]), "+f"(d[10]), "+f"(d[11]),
      "+f"(d[12]), "+f"(d[13]), "+f"(d[14]), "+f"(d[15]), "+f"(d[16]), "+f"(d[17]), "+f"(d[18]), "+f"(d[19]), "+f"(d[20]), "+f"(d[21]), "+f"(d[22]), "+f"(d[23]),
      "+f"(d[24]), "+f"(d[25]), "+f"(d[26]), "+f"(d[27]), "+f"(d[28]), "+f"(d[29]), "+f"(d[30]), "+f"(d[31])
    : "r"(a[0]), "r"(a[1]), "r"(a[2]), "r"(a[3]), "l"(b));
  else asm volatile("wgmma.mma_async.sync.aligned.m64n64k16.f32.bf16.bf16 {%0,%1,%2,%3,%4,%5,%6,%7,%8,%9,%10,%11,%12,%13,%14,%15,%16,%17,%18,%19,%20,%21,%22,%23,%24,%25,%26,%27,%28,%29,%30,%31},{%32,%33,%34,%35},%36,0,1,1,0;"
    : "=f"(d[0]), "=f"(d[1]), "=f"(d[2]), "=f"(d[3]), "=f"(d[4]), "=f"(d[5]), "=f"(d[6]), "=f"(d[7]), "=f"(d[8]), "=f"(d[9]), "=f"(d[10]), "=f"(d[11]),
      "=f"(d[12]), "=f"(d[13]), "=f"(d[14]), "=f"(d[15]), "=f"(d[16]), "=f"(d[17]), "=f"(d[18]), "=f"(d[19]), "=f"(d[20]), "=f"(d[21]), "=f"(d[22]), "=f"(d[23]),
      "=f"(d[24]), "=f"(d[25]), "=f"(d[26]), "=f"(d[27]), "=f"(d[28]), "=f"(d[29]), "=f"(d[30]), "=f"(d[31])
    : "r"(a[0]), "r"(a[1]), "r"(a[2]), "r"(a[3]), "l"(b));
}

template<int ACC> __device__ __forceinline__ void ss24tn(float* d, uint64_t a, uint64_t b) {
  if (ACC) asm volatile("wgmma.mma_async.sync.aligned.m64n24k16.f32.bf16.bf16 {%0,%1,%2,%3,%4,%5,%6,%7,%8,%9,%10,%11},%12,%13,1,1,1,1,0;"
    : "+f"(d[0]), "+f"(d[1]), "+f"(d[2]), "+f"(d[3]), "+f"(d[4]), "+f"(d[5]), "+f"(d[6]), "+f"(d[7]), "+f"(d[8]), "+f"(d[9]), "+f"(d[10]), "+f"(d[11])
    : "l"(a), "l"(b));
  else asm volatile("wgmma.mma_async.sync.aligned.m64n24k16.f32.bf16.bf16 {%0,%1,%2,%3,%4,%5,%6,%7,%8,%9,%10,%11},%12,%13,0,1,1,1,0;"
    : "=f"(d[0]), "=f"(d[1]), "=f"(d[2]), "=f"(d[3]), "=f"(d[4]), "=f"(d[5]), "=f"(d[6]), "=f"(d[7]), "=f"(d[8]), "=f"(d[9]), "=f"(d[10]), "=f"(d[11])
    : "l"(a), "l"(b));
}

template<int ACC> __device__ __forceinline__ void ss32tn(float* d, uint64_t a, uint64_t b) {
  if (ACC) asm volatile("wgmma.mma_async.sync.aligned.m64n32k16.f32.bf16.bf16 {%0,%1,%2,%3,%4,%5,%6,%7,%8,%9,%10,%11,%12,%13,%14,%15},%16,%17,1,1,1,1,0;"
    : "+f"(d[0]), "+f"(d[1]), "+f"(d[2]), "+f"(d[3]), "+f"(d[4]), "+f"(d[5]), "+f"(d[6]), "+f"(d[7]), "+f"(d[8]), "+f"(d[9]), "+f"(d[10]), "+f"(d[11]),
      "+f"(d[12]), "+f"(d[13]), "+f"(d[14]), "+f"(d[15])
    : "l"(a), "l"(b));
  else asm volatile("wgmma.mma_async.sync.aligned.m64n32k16.f32.bf16.bf16 {%0,%1,%2,%3,%4,%5,%6,%7,%8,%9,%10,%11,%12,%13,%14,%15},%16,%17,0,1,1,1,0;"
    : "=f"(d[0]), "=f"(d[1]), "=f"(d[2]), "=f"(d[3]), "=f"(d[4]), "=f"(d[5]), "=f"(d[6]), "=f"(d[7]), "=f"(d[8]), "=f"(d[9]), "=f"(d[10]), "=f"(d[11]),
      "=f"(d[12]), "=f"(d[13]), "=f"(d[14]), "=f"(d[15])
    : "l"(a), "l"(b));
}

template<int ACC> __device__ __forceinline__ void ss48tn(float* d, uint64_t a, uint64_t b) {
  if (ACC) asm volatile("wgmma.mma_async.sync.aligned.m64n48k16.f32.bf16.bf16 {%0,%1,%2,%3,%4,%5,%6,%7,%8,%9,%10,%11,%12,%13,%14,%15,%16,%17,%18,%19,%20,%21,%22,%23},%24,%25,1,1,1,1,0;"
    : "+f"(d[0]), "+f"(d[1]), "+f"(d[2]), "+f"(d[3]), "+f"(d[4]), "+f"(d[5]), "+f"(d[6]), "+f"(d[7]), "+f"(d[8]), "+f"(d[9]), "+f"(d[10]), "+f"(d[11]),
      "+f"(d[12]), "+f"(d[13]), "+f"(d[14]), "+f"(d[15]), "+f"(d[16]), "+f"(d[17]), "+f"(d[18]), "+f"(d[19]), "+f"(d[20]), "+f"(d[21]), "+f"(d[22]), "+f"(d[23])
    : "l"(a), "l"(b));
  else asm volatile("wgmma.mma_async.sync.aligned.m64n48k16.f32.bf16.bf16 {%0,%1,%2,%3,%4,%5,%6,%7,%8,%9,%10,%11,%12,%13,%14,%15,%16,%17,%18,%19,%20,%21,%22,%23},%24,%25,0,1,1,1,0;"
    : "=f"(d[0]), "=f"(d[1]), "=f"(d[2]), "=f"(d[3]), "=f"(d[4]), "=f"(d[5]), "=f"(d[6]), "=f"(d[7]), "=f"(d[8]), "=f"(d[9]), "=f"(d[10]), "=f"(d[11]),
      "=f"(d[12]), "=f"(d[13]), "=f"(d[14]), "=f"(d[15]), "=f"(d[16]), "=f"(d[17]), "=f"(d[18]), "=f"(d[19]), "=f"(d[20]), "=f"(d[21]), "=f"(d[22]), "=f"(d[23])
    : "l"(a), "l"(b));
}

template<int ACC> __device__ __forceinline__ void ss56tn(float* d, uint64_t a, uint64_t b) {
  if (ACC) asm volatile("wgmma.mma_async.sync.aligned.m64n56k16.f32.bf16.bf16 {%0,%1,%2,%3,%4,%5,%6,%7,%8,%9,%10,%11,%12,%13,%14,%15,%16,%17,%18,%19,%20,%21,%22,%23,%24,%25,%26,%27},%28,%29,1,1,1,1,0;"
    : "+f"(d[0]), "+f"(d[1]), "+f"(d[2]), "+f"(d[3]), "+f"(d[4]), "+f"(d[5]), "+f"(d[6]), "+f"(d[7]), "+f"(d[8]), "+f"(d[9]), "+f"(d[10]), "+f"(d[11]),
      "+f"(d[12]), "+f"(d[13]), "+f"(d[14]), "+f"(d[15]), "+f"(d[16]), "+f"(d[17]), "+f"(d[18]), "+f"(d[19]), "+f"(d[20]), "+f"(d[21]), "+f"(d[22]), "+f"(d[23]),
      "+f"(d[24]), "+f"(d[25]), "+f"(d[26]), "+f"(d[27])
    : "l"(a), "l"(b));
  else asm volatile("wgmma.mma_async.sync.aligned.m64n56k16.f32.bf16.bf16 {%0,%1,%2,%3,%4,%5,%6,%7,%8,%9,%10,%11,%12,%13,%14,%15,%16,%17,%18,%19,%20,%21,%22,%23,%24,%25,%26,%27},%28,%29,0,1,1,1,0;"
    : "=f"(d[0]), "=f"(d[1]), "=f"(d[2]), "=f"(d[3]), "=f"(d[4]), "=f"(d[5]), "=f"(d[6]), "=f"(d[7]), "=f"(d[8]), "=f"(d[9]), "=f"(d[10]), "=f"(d[11]),
      "=f"(d[12]), "=f"(d[13]), "=f"(d[14]), "=f"(d[15]), "=f"(d[16]), "=f"(d[17]), "=f"(d[18]), "=f"(d[19]), "=f"(d[20]), "=f"(d[21]), "=f"(d[22]), "=f"(d[23]),
      "=f"(d[24]), "=f"(d[25]), "=f"(d[26]), "=f"(d[27])
    : "l"(a), "l"(b));
}

template<int ACC> __device__ __forceinline__ void ss40tt(float* d, uint64_t a, uint64_t b) {
  if (ACC) asm volatile("wgmma.mma_async.sync.aligned.m64n40k16.f32.bf16.bf16 {%0,%1,%2,%3,%4,%5,%6,%7,%8,%9,%10,%11,%12,%13,%14,%15,%16,%17,%18,%19},%20,%21,1,1,1,1,1;"
    : "+f"(d[0]), "+f"(d[1]), "+f"(d[2]), "+f"(d[3]), "+f"(d[4]), "+f"(d[5]), "+f"(d[6]), "+f"(d[7]), "+f"(d[8]), "+f"(d[9]), "+f"(d[10]), "+f"(d[11]),
      "+f"(d[12]), "+f"(d[13]), "+f"(d[14]), "+f"(d[15]), "+f"(d[16]), "+f"(d[17]), "+f"(d[18]), "+f"(d[19])
    : "l"(a), "l"(b));
  else asm volatile("wgmma.mma_async.sync.aligned.m64n40k16.f32.bf16.bf16 {%0,%1,%2,%3,%4,%5,%6,%7,%8,%9,%10,%11,%12,%13,%14,%15,%16,%17,%18,%19},%20,%21,0,1,1,1,1;"
    : "=f"(d[0]), "=f"(d[1]), "=f"(d[2]), "=f"(d[3]), "=f"(d[4]), "=f"(d[5]), "=f"(d[6]), "=f"(d[7]), "=f"(d[8]), "=f"(d[9]), "=f"(d[10]), "=f"(d[11]),
      "=f"(d[12]), "=f"(d[13]), "=f"(d[14]), "=f"(d[15]), "=f"(d[16]), "=f"(d[17]), "=f"(d[18]), "=f"(d[19])
    : "l"(a), "l"(b));
}

template<int ACC> __device__ __forceinline__ void rs144t(float* d, const uint32_t* a, uint64_t b) {
  if (ACC) asm volatile("wgmma.mma_async.sync.aligned.m64n144k16.f32.bf16.bf16 {%0,%1,%2,%3,%4,%5,%6,%7,%8,%9,%10,%11,%12,%13,%14,%15,%16,%17,%18,%19,%20,%21,%22,%23,%24,%25,%26,%27,%28,%29,%30,%31,%32,%33,%34,%35,%36,%37,%38,%39,%40,%41,%42,%43,%44,%45,%46,%47,%48,%49,%50,%51,%52,%53,%54,%55,%56,%57,%58,%59,%60,%61,%62,%63,%64,%65,%66,%67,%68,%69,%70,%71},{%72,%73,%74,%75},%76,1,1,1,1;"
    : "+f"(d[0]), "+f"(d[1]), "+f"(d[2]), "+f"(d[3]), "+f"(d[4]), "+f"(d[5]), "+f"(d[6]), "+f"(d[7]), "+f"(d[8]), "+f"(d[9]), "+f"(d[10]), "+f"(d[11]),
      "+f"(d[12]), "+f"(d[13]), "+f"(d[14]), "+f"(d[15]), "+f"(d[16]), "+f"(d[17]), "+f"(d[18]), "+f"(d[19]), "+f"(d[20]), "+f"(d[21]), "+f"(d[22]), "+f"(d[23]),
      "+f"(d[24]), "+f"(d[25]), "+f"(d[26]), "+f"(d[27]), "+f"(d[28]), "+f"(d[29]), "+f"(d[30]), "+f"(d[31]), "+f"(d[32]), "+f"(d[33]), "+f"(d[34]), "+f"(d[35]),
      "+f"(d[36]), "+f"(d[37]), "+f"(d[38]), "+f"(d[39]), "+f"(d[40]), "+f"(d[41]), "+f"(d[42]), "+f"(d[43]), "+f"(d[44]), "+f"(d[45]), "+f"(d[46]), "+f"(d[47]),
      "+f"(d[48]), "+f"(d[49]), "+f"(d[50]), "+f"(d[51]), "+f"(d[52]), "+f"(d[53]), "+f"(d[54]), "+f"(d[55]), "+f"(d[56]), "+f"(d[57]), "+f"(d[58]), "+f"(d[59]),
      "+f"(d[60]), "+f"(d[61]), "+f"(d[62]), "+f"(d[63]), "+f"(d[64]), "+f"(d[65]), "+f"(d[66]), "+f"(d[67]), "+f"(d[68]), "+f"(d[69]), "+f"(d[70]), "+f"(d[71])
    : "r"(a[0]), "r"(a[1]), "r"(a[2]), "r"(a[3]), "l"(b));
  else asm volatile("wgmma.mma_async.sync.aligned.m64n144k16.f32.bf16.bf16 {%0,%1,%2,%3,%4,%5,%6,%7,%8,%9,%10,%11,%12,%13,%14,%15,%16,%17,%18,%19,%20,%21,%22,%23,%24,%25,%26,%27,%28,%29,%30,%31,%32,%33,%34,%35,%36,%37,%38,%39,%40,%41,%42,%43,%44,%45,%46,%47,%48,%49,%50,%51,%52,%53,%54,%55,%56,%57,%58,%59,%60,%61,%62,%63,%64,%65,%66,%67,%68,%69,%70,%71},{%72,%73,%74,%75},%76,0,1,1,1;"
    : "=f"(d[0]), "=f"(d[1]), "=f"(d[2]), "=f"(d[3]), "=f"(d[4]), "=f"(d[5]), "=f"(d[6]), "=f"(d[7]), "=f"(d[8]), "=f"(d[9]), "=f"(d[10]), "=f"(d[11]),
      "=f"(d[12]), "=f"(d[13]), "=f"(d[14]), "=f"(d[15]), "=f"(d[16]), "=f"(d[17]), "=f"(d[18]), "=f"(d[19]), "=f"(d[20]), "=f"(d[21]), "=f"(d[22]), "=f"(d[23]),
      "=f"(d[24]), "=f"(d[25]), "=f"(d[26]), "=f"(d[27]), "=f"(d[28]), "=f"(d[29]), "=f"(d[30]), "=f"(d[31]), "=f"(d[32]), "=f"(d[33]), "=f"(d[34]), "=f"(d[35]),
      "=f"(d[36]), "=f"(d[37]), "=f"(d[38]), "=f"(d[39]), "=f"(d[40]), "=f"(d[41]), "=f"(d[42]), "=f"(d[43]), "=f"(d[44]), "=f"(d[45]), "=f"(d[46]), "=f"(d[47]),
      "=f"(d[48]), "=f"(d[49]), "=f"(d[50]), "=f"(d[51]), "=f"(d[52]), "=f"(d[53]), "=f"(d[54]), "=f"(d[55]), "=f"(d[56]), "=f"(d[57]), "=f"(d[58]), "=f"(d[59]),
      "=f"(d[60]), "=f"(d[61]), "=f"(d[62]), "=f"(d[63]), "=f"(d[64]), "=f"(d[65]), "=f"(d[66]), "=f"(d[67]), "=f"(d[68]), "=f"(d[69]), "=f"(d[70]), "=f"(d[71])
    : "r"(a[0]), "r"(a[1]), "r"(a[2]), "r"(a[3]), "l"(b));
}

template<int ACC> __device__ __forceinline__ void rs168t(float* d, const uint32_t* a, uint64_t b) {
  if (ACC) asm volatile("wgmma.mma_async.sync.aligned.m64n168k16.f32.bf16.bf16 {%0,%1,%2,%3,%4,%5,%6,%7,%8,%9,%10,%11,%12,%13,%14,%15,%16,%17,%18,%19,%20,%21,%22,%23,%24,%25,%26,%27,%28,%29,%30,%31,%32,%33,%34,%35,%36,%37,%38,%39,%40,%41,%42,%43,%44,%45,%46,%47,%48,%49,%50,%51,%52,%53,%54,%55,%56,%57,%58,%59,%60,%61,%62,%63,%64,%65,%66,%67,%68,%69,%70,%71,%72,%73,%74,%75,%76,%77,%78,%79,%80,%81,%82,%83},{%84,%85,%86,%87},%88,1,1,1,1;"
    : "+f"(d[0]), "+f"(d[1]), "+f"(d[2]), "+f"(d[3]), "+f"(d[4]), "+f"(d[5]), "+f"(d[6]), "+f"(d[7]), "+f"(d[8]), "+f"(d[9]), "+f"(d[10]), "+f"(d[11]),
      "+f"(d[12]), "+f"(d[13]), "+f"(d[14]), "+f"(d[15]), "+f"(d[16]), "+f"(d[17]), "+f"(d[18]), "+f"(d[19]), "+f"(d[20]), "+f"(d[21]), "+f"(d[22]), "+f"(d[23]),
      "+f"(d[24]), "+f"(d[25]), "+f"(d[26]), "+f"(d[27]), "+f"(d[28]), "+f"(d[29]), "+f"(d[30]), "+f"(d[31]), "+f"(d[32]), "+f"(d[33]), "+f"(d[34]), "+f"(d[35]),
      "+f"(d[36]), "+f"(d[37]), "+f"(d[38]), "+f"(d[39]), "+f"(d[40]), "+f"(d[41]), "+f"(d[42]), "+f"(d[43]), "+f"(d[44]), "+f"(d[45]), "+f"(d[46]), "+f"(d[47]),
      "+f"(d[48]), "+f"(d[49]), "+f"(d[50]), "+f"(d[51]), "+f"(d[52]), "+f"(d[53]), "+f"(d[54]), "+f"(d[55]), "+f"(d[56]), "+f"(d[57]), "+f"(d[58]), "+f"(d[59]),
      "+f"(d[60]), "+f"(d[61]), "+f"(d[62]), "+f"(d[63]), "+f"(d[64]), "+f"(d[65]), "+f"(d[66]), "+f"(d[67]), "+f"(d[68]), "+f"(d[69]), "+f"(d[70]), "+f"(d[71]),
      "+f"(d[72]), "+f"(d[73]), "+f"(d[74]), "+f"(d[75]), "+f"(d[76]), "+f"(d[77]), "+f"(d[78]), "+f"(d[79]), "+f"(d[80]), "+f"(d[81]), "+f"(d[82]), "+f"(d[83])
    : "r"(a[0]), "r"(a[1]), "r"(a[2]), "r"(a[3]), "l"(b));
  else asm volatile("wgmma.mma_async.sync.aligned.m64n168k16.f32.bf16.bf16 {%0,%1,%2,%3,%4,%5,%6,%7,%8,%9,%10,%11,%12,%13,%14,%15,%16,%17,%18,%19,%20,%21,%22,%23,%24,%25,%26,%27,%28,%29,%30,%31,%32,%33,%34,%35,%36,%37,%38,%39,%40,%41,%42,%43,%44,%45,%46,%47,%48,%49,%50,%51,%52,%53,%54,%55,%56,%57,%58,%59,%60,%61,%62,%63,%64,%65,%66,%67,%68,%69,%70,%71,%72,%73,%74,%75,%76,%77,%78,%79,%80,%81,%82,%83},{%84,%85,%86,%87},%88,0,1,1,1;"
    : "=f"(d[0]), "=f"(d[1]), "=f"(d[2]), "=f"(d[3]), "=f"(d[4]), "=f"(d[5]), "=f"(d[6]), "=f"(d[7]), "=f"(d[8]), "=f"(d[9]), "=f"(d[10]), "=f"(d[11]),
      "=f"(d[12]), "=f"(d[13]), "=f"(d[14]), "=f"(d[15]), "=f"(d[16]), "=f"(d[17]), "=f"(d[18]), "=f"(d[19]), "=f"(d[20]), "=f"(d[21]), "=f"(d[22]), "=f"(d[23]),
      "=f"(d[24]), "=f"(d[25]), "=f"(d[26]), "=f"(d[27]), "=f"(d[28]), "=f"(d[29]), "=f"(d[30]), "=f"(d[31]), "=f"(d[32]), "=f"(d[33]), "=f"(d[34]), "=f"(d[35]),
      "=f"(d[36]), "=f"(d[37]), "=f"(d[38]), "=f"(d[39]), "=f"(d[40]), "=f"(d[41]), "=f"(d[42]), "=f"(d[43]), "=f"(d[44]), "=f"(d[45]), "=f"(d[46]), "=f"(d[47]),
      "=f"(d[48]), "=f"(d[49]), "=f"(d[50]), "=f"(d[51]), "=f"(d[52]), "=f"(d[53]), "=f"(d[54]), "=f"(d[55]), "=f"(d[56]), "=f"(d[57]), "=f"(d[58]), "=f"(d[59]),
      "=f"(d[60]), "=f"(d[61]), "=f"(d[62]), "=f"(d[63]), "=f"(d[64]), "=f"(d[65]), "=f"(d[66]), "=f"(d[67]), "=f"(d[68]), "=f"(d[69]), "=f"(d[70]), "=f"(d[71]),
      "=f"(d[72]), "=f"(d[73]), "=f"(d[74]), "=f"(d[75]), "=f"(d[76]), "=f"(d[77]), "=f"(d[78]), "=f"(d[79]), "=f"(d[80]), "=f"(d[81]), "=f"(d[82]), "=f"(d[83])
    : "r"(a[0]), "r"(a[1]), "r"(a[2]), "r"(a[3]), "l"(b));
}

template<int ACC> __device__ __forceinline__ void rs192t(float* d, const uint32_t* a, uint64_t b) {
  if (ACC) asm volatile("wgmma.mma_async.sync.aligned.m64n192k16.f32.bf16.bf16 {%0,%1,%2,%3,%4,%5,%6,%7,%8,%9,%10,%11,%12,%13,%14,%15,%16,%17,%18,%19,%20,%21,%22,%23,%24,%25,%26,%27,%28,%29,%30,%31,%32,%33,%34,%35,%36,%37,%38,%39,%40,%41,%42,%43,%44,%45,%46,%47,%48,%49,%50,%51,%52,%53,%54,%55,%56,%57,%58,%59,%60,%61,%62,%63,%64,%65,%66,%67,%68,%69,%70,%71,%72,%73,%74,%75,%76,%77,%78,%79,%80,%81,%82,%83,%84,%85,%86,%87,%88,%89,%90,%91,%92,%93,%94,%95},{%96,%97,%98,%99},%100,1,1,1,1;"
    : "+f"(d[0]), "+f"(d[1]), "+f"(d[2]), "+f"(d[3]), "+f"(d[4]), "+f"(d[5]), "+f"(d[6]), "+f"(d[7]), "+f"(d[8]), "+f"(d[9]), "+f"(d[10]), "+f"(d[11]),
      "+f"(d[12]), "+f"(d[13]), "+f"(d[14]), "+f"(d[15]), "+f"(d[16]), "+f"(d[17]), "+f"(d[18]), "+f"(d[19]), "+f"(d[20]), "+f"(d[21]), "+f"(d[22]), "+f"(d[23]),
      "+f"(d[24]), "+f"(d[25]), "+f"(d[26]), "+f"(d[27]), "+f"(d[28]), "+f"(d[29]), "+f"(d[30]), "+f"(d[31]), "+f"(d[32]), "+f"(d[33]), "+f"(d[34]), "+f"(d[35]),
      "+f"(d[36]), "+f"(d[37]), "+f"(d[38]), "+f"(d[39]), "+f"(d[40]), "+f"(d[41]), "+f"(d[42]), "+f"(d[43]), "+f"(d[44]), "+f"(d[45]), "+f"(d[46]), "+f"(d[47]),
      "+f"(d[48]), "+f"(d[49]), "+f"(d[50]), "+f"(d[51]), "+f"(d[52]), "+f"(d[53]), "+f"(d[54]), "+f"(d[55]), "+f"(d[56]), "+f"(d[57]), "+f"(d[58]), "+f"(d[59]),
      "+f"(d[60]), "+f"(d[61]), "+f"(d[62]), "+f"(d[63]), "+f"(d[64]), "+f"(d[65]), "+f"(d[66]), "+f"(d[67]), "+f"(d[68]), "+f"(d[69]), "+f"(d[70]), "+f"(d[71]),
      "+f"(d[72]), "+f"(d[73]), "+f"(d[74]), "+f"(d[75]), "+f"(d[76]), "+f"(d[77]), "+f"(d[78]), "+f"(d[79]), "+f"(d[80]), "+f"(d[81]), "+f"(d[82]), "+f"(d[83]),
      "+f"(d[84]), "+f"(d[85]), "+f"(d[86]), "+f"(d[87]), "+f"(d[88]), "+f"(d[89]), "+f"(d[90]), "+f"(d[91]), "+f"(d[92]), "+f"(d[93]), "+f"(d[94]), "+f"(d[95])
    : "r"(a[0]), "r"(a[1]), "r"(a[2]), "r"(a[3]), "l"(b));
  else asm volatile("wgmma.mma_async.sync.aligned.m64n192k16.f32.bf16.bf16 {%0,%1,%2,%3,%4,%5,%6,%7,%8,%9,%10,%11,%12,%13,%14,%15,%16,%17,%18,%19,%20,%21,%22,%23,%24,%25,%26,%27,%28,%29,%30,%31,%32,%33,%34,%35,%36,%37,%38,%39,%40,%41,%42,%43,%44,%45,%46,%47,%48,%49,%50,%51,%52,%53,%54,%55,%56,%57,%58,%59,%60,%61,%62,%63,%64,%65,%66,%67,%68,%69,%70,%71,%72,%73,%74,%75,%76,%77,%78,%79,%80,%81,%82,%83,%84,%85,%86,%87,%88,%89,%90,%91,%92,%93,%94,%95},{%96,%97,%98,%99},%100,0,1,1,1;"
    : "=f"(d[0]), "=f"(d[1]), "=f"(d[2]), "=f"(d[3]), "=f"(d[4]), "=f"(d[5]), "=f"(d[6]), "=f"(d[7]), "=f"(d[8]), "=f"(d[9]), "=f"(d[10]), "=f"(d[11]),
      "=f"(d[12]), "=f"(d[13]), "=f"(d[14]), "=f"(d[15]), "=f"(d[16]), "=f"(d[17]), "=f"(d[18]), "=f"(d[19]), "=f"(d[20]), "=f"(d[21]), "=f"(d[22]), "=f"(d[23]),
      "=f"(d[24]), "=f"(d[25]), "=f"(d[26]), "=f"(d[27]), "=f"(d[28]), "=f"(d[29]), "=f"(d[30]), "=f"(d[31]), "=f"(d[32]), "=f"(d[33]), "=f"(d[34]), "=f"(d[35]),
      "=f"(d[36]), "=f"(d[37]), "=f"(d[38]), "=f"(d[39]), "=f"(d[40]), "=f"(d[41]), "=f"(d[42]), "=f"(d[43]), "=f"(d[44]), "=f"(d[45]), "=f"(d[46]), "=f"(d[47]),
      "=f"(d[48]), "=f"(d[49]), "=f"(d[50]), "=f"(d[51]), "=f"(d[52]), "=f"(d[53]), "=f"(d[54]), "=f"(d[55]), "=f"(d[56]), "=f"(d[57]), "=f"(d[58]), "=f"(d[59]),
      "=f"(d[60]), "=f"(d[61]), "=f"(d[62]), "=f"(d[63]), "=f"(d[64]), "=f"(d[65]), "=f"(d[66]), "=f"(d[67]), "=f"(d[68]), "=f"(d[69]), "=f"(d[70]), "=f"(d[71]),
      "=f"(d[72]), "=f"(d[73]), "=f"(d[74]), "=f"(d[75]), "=f"(d[76]), "=f"(d[77]), "=f"(d[78]), "=f"(d[79]), "=f"(d[80]), "=f"(d[81]), "=f"(d[82]), "=f"(d[83]),
      "=f"(d[84]), "=f"(d[85]), "=f"(d[86]), "=f"(d[87]), "=f"(d[88]), "=f"(d[89]), "=f"(d[90]), "=f"(d[91]), "=f"(d[92]), "=f"(d[93]), "=f"(d[94]), "=f"(d[95])
    : "r"(a[0]), "r"(a[1]), "r"(a[2]), "r"(a[3]), "l"(b));
}

template<int NP> __device__ __forceinline__ float4 row_stats(const uint32_t (*y)[4]) {
  float m[2], q[2];
#pragma unroll
  for (int r = 0; r < 2; r++) {
    m[r] = 0.f;
#pragma unroll
    for (int i = 0; i < NP; i++) m[r] += (blo(y[i][r]) + bhi(y[i][r])) + (blo(y[i][r + 2]) + bhi(y[i][r + 2]));
  }
#pragma unroll
  for (int o = 1; o < 4; o *= 2) { m[0] += __shfl_xor_sync(~0u, m[0], o); m[1] += __shfl_xor_sync(~0u, m[1], o); }
#pragma unroll
  for (int r = 0; r < 2; r++) {
    m[r] *= (1.f / (16 * NP)); q[r] = 0.f;
#pragma unroll
    for (int i = 0; i < 2 * NP; i++) { const uint32_t v = y[i >> 1][r + (i & 1) * 2]; const float a = blo(v) - m[r], b = bhi(v) - m[r]; q[r] += a * a + b * b; }
  }
#pragma unroll
  for (int o = 1; o < 4; o *= 2) { q[0] += __shfl_xor_sync(~0u, q[0], o); q[1] += __shfl_xor_sync(~0u, q[1], o); }
  return make_float4(m[0], q[0], m[1], q[1]);
}

constexpr uint32_t PL = 9472, PG = 9216;
constexpr uint32_t H_MEM = 0, H_QB = 94720, H_KB = 104960, H_VB = 115200, H_ZERO = H_VB + 10240, H_OS = 127488, H_ST = 135680, H_OM = 143872,
                   H_WO = 152320, H_DUMP = 203520, H_BAR = 203648, H_LN = 203904, H_WL = 204672, H_TRC = 147968;
constexpr uint32_t H_SMEM = H_WL + 6 * 4096;
constexpr int KR = KRV;
constexpr uint32_t WLS = (37 - KR) * 256;
constexpr int NM = 16 + 8 * EX, NB = 64 - 8 * EX;
constexpr uint32_t B_MEM = H_BAR, B_XT = H_BAR + 32, B_XB = H_BAR + 40, B_MD = H_BAR + 48, B_QK = H_BAR + 64, B_V = H_BAR + 72,
                   B_OM = H_BAR + 80, B_W2 = H_BAR + 88, B_W3 = H_BAR + 96, B_OS = H_BAR + 104, B_ST = H_BAR + 112, B_XA = H_BAR + 120, B_WS = H_BAR + 56, B_XC = H_BAR + 128;

__device__ __forceinline__ void cluster_sync() { asm volatile("barrier.cluster.arrive.release.aligned; barrier.cluster.wait.acquire.aligned;" ::: "memory"); }

template<int N, int KK> __device__ __forceinline__ void proj_step(float* acc, const uint32_t* w, uint64_t d, uint64_t wl) {
  constexpr int A = KK != 36;
  if constexpr (KK < KR) {
    if (N == 24) rs24<A>(acc, &w[KK * 4], d + KK * 16); if (N == 32) rs32<A>(acc, &w[KK * 4], d + KK * 16);
    if (N == 48) rs48<A>(acc, &w[KK * 4], d + KK * 16); if (N == 56) rs56<A>(acc, &w[KK * 4], d + KK * 16);
  } else {
    if (N == 24) ss24tn<A>(acc, wl + (KK - KR) * 16, d + KK * 16); if (N == 32) ss32tn<A>(acc, wl + (KK - KR) * 16, d + KK * 16);
    if (N == 48) ss48tn<A>(acc, wl + (KK - KR) * 16, d + KK * 16); if (N == 56) ss56tn<A>(acc, wl + (KK - KR) * 16, d + KK * 16);
  }
}
template<int N, int K0, int K1> __device__ __forceinline__ void proj_loop(float* acc, const uint32_t* w, uint64_t d, uint64_t wl) {
  if constexpr (K0 < K1) { proj_step<N, K0>(acc, w, d, wl); proj_loop<N, K0 + 1, K1>(acc, w, d, wl); }
}
template<int N, int K0, int K1> __device__ __forceinline__ void proj_steps(float* acc, const uint32_t* w, uint64_t d, uint64_t wl) {
  if constexpr (K0 < K1) { wg_fence(); proj_loop<N, K0, K1>(acc, w, d, wl); wg_commit(); }
}

template<int J> __device__ __forceinline__ void h_proj(const uint32_t sb, const int wg, const int w, const int lane) {
  uint32_t wr[KR * 4];
  {
    const uint32_t a = sb + (wg * 8 + w * 2 + ((lane >> 3) & 1)) * 16 + ((lane >> 4) * 8 + (lane & 7)) * 272;
#pragma unroll
    for (int kk = 0; kk < KR; kk++) ldsm4t(&wr[kk * 4], a + kk * 16 * 272);
  }
  float cs0 = 0.f, cs1 = 0.f;
#pragma unroll
  for (int kk = 0; kk < 36; kk++) {
    uint32_t t[4];
    if (kk >= KR) ldsm4t(t, sb + H_WL + (wg * 8 + w * 2 + ((lane >> 3) & 1)) * WLS + ((kk - KR) * 16 + (lane >> 4) * 8 + (lane & 7)) * 16);
    const uint32_t* a = kk < KR ? &wr[kk * 4] : t;
    cs0 += (blo(a[0]) + bhi(a[0])) + (blo(a[2]) + bhi(a[2])); cs1 += (blo(a[1]) + bhi(a[1])) + (blo(a[3]) + bhi(a[3]));
  }
#pragma unroll
  for (int o = 1; o < 4; o *= 2) { cs0 += __shfl_xor_sync(~0u, cs0, o); cs1 += __shfl_xor_sync(~0u, cs1, o); }
  {
    const uint32_t a = sb + H_WL + (wg * 8 + w * 2) * WLS + (36 - KR) * 256;
    sts4(a + (lane >> 4) * WLS + (lane & 15) * 16, 0, 0, 0, 0);
    __syncwarp();
    const uint32_t hi = pk(cs0, cs1), lo = pk(cs0 - blo(hi), cs1 - bhi(hi)), v = (lane & 3) == 1 ? lo : hi;
    if ((lane & 3) < 3) {
      asm volatile("st.shared.b16 [%0], %1;" :: "r"(a + (lane & 3) * 16 + (lane >> 2) * 2), "h"((uint16_t)v) : "memory");
      asm volatile("st.shared.b16 [%0], %1;" :: "r"(a + WLS + (lane & 3) * 16 + (lane >> 2) * 2), "h"((uint16_t)(v >> 16)) : "memory");
    }
    fence_async();
  }
  asm volatile("bar.sync 1, 512;" ::: "memory");
  cluster_sync();
  constexpr uint32_t BUF = J == 0 ? H_QB : J == 1 ? H_KB : H_VB, BAR = J == 2 ? B_V : B_QK;
  const uint32_t so = sb & 0x1FFFFFF;
  const uint32_t dst = so + BUF + 8192 + (wg * 8 + w * 2) * 128 + lane * 4;
  const uint64_t wl = mkdesc(sb + H_WL + wg * 8 * WLS, 128, WLS);
  const uint64_t md = mkdesc(sb + H_MEM, 128, PL);
  static_assert(EX == 2, "token blocks are normalised in pairs");
  uint32_t pt[4];
  auto scale = [&](uint32_t* p, const float* a, const float4 r) {
    p[0] = pk(a[0] * r.x, a[1] * r.y); p[1] = pk(a[2] * r.x, a[3] * r.y); p[2] = pk(a[4] * r.z, a[5] * r.w); p[3] = pk(a[6] * r.z, a[7] * r.w);
  };
  const uint32_t lna = sb + H_LN + (lane & 3) * 32;
  auto put = [&](const uint32_t* p) {
    const uint32_t a = sb + (wg * 8 + w * 2) * 128 + (lane >> 3) * 2048 + (lane & 7) * 16;
#pragma unroll
    for (int L = 0; L < 2; L++) {
      const uint32_t b = a + (J == 2 ? (L ? H_KB : H_QB) : L == J ? BUF : H_ST);
      stsm4(b, p[8 * L], p[8 * L + 2], p[8 * L + 4], p[8 * L + 6]);
      stsm4(b + 128, p[8 * L + 1], p[8 * L + 3], p[8 * L + 5], p[8 * L + 7]);
    }
    publish(sb + B_ST, sb + H_ZERO, lane);
  };
  {
    float acc[16];
    mbar_wait(sb + B_XB, 0);
    proj_steps<32, 36, 37>(acc, wr, md + 6 * (PL / 16), wl);
    proj_steps<32, 0, 36>(acc, wr, md + 6 * (PL / 16), wl);
    wg_wait<0>(); pin<16>(acc);
    uint32_t p[16];
#pragma unroll
    for (int i = 0; i < 2; i++) scale(&p[4 * i], &acc[8 * i], lds_f4(lna + i * 16));
#pragma unroll
    for (int i = 0; i < 8; i++) p[8 + i] = p[i];
    put(p);
    mbar_wait(sb + B_XT, 0);
  }
  for (int s = 0;; s++) {
    float accM[NM / 2], accB[NB / 2];
    proj_steps<NM, 36, 37>(accM, wr, md, wl);
    mbar_wait(sb + B_MEM, s & 1);
    if (wg == 0) { TR(0); }
    proj_steps<NM, 0, 9>(accM, wr, md, wl);
    mbar_wait(sb + B_MEM + 8, s & 1);
    proj_steps<NM, 9, 18>(accM, wr, md, wl);
    mbar_wait(sb + B_MEM + 16, s & 1);
    proj_steps<NM, 18, 27>(accM, wr, md, wl);
    mbar_wait(sb + B_MEM + 24, s & 1);
    if (wg == 0) { TR(6); }
    proj_steps<NM, 27, 36>(accM, wr, md, wl);
    if (lane == 0) mbar_arrive(sb + B_XC);
    const uint32_t lnf = lna + ((s + 1) & 1) * 128;
    const float4 rt = lds_f4(lnf);
    wg_wait<0>(); pin<NM / 2>(accM);
#pragma unroll
    for (int L = 0; L < 2; L++) if (L != J) {
      st_async1(dst + (L << 25), pk(accM[4 * L], accM[4 * L + 1]), so + BAR + (L << 25));
      st_async1(dst + (L << 25) + 128, pk(accM[4 * L + 2], accM[4 * L + 3]), so + BAR + (L << 25));
    }
    if (J < 2) {
      sts1(dst + (J << 25), pk(accM[4 * J], accM[4 * J + 1])); sts1(dst + (J << 25) + 128, pk(accM[4 * J + 2], accM[4 * J + 3]));
      publish(sb + B_QK, sb + H_ZERO, lane);
    }
    TR(1 + wg * 4);
    if (s == NSTEP - 1) break;
    if (lane == 0) mbar_arrive(sb + B_MD);
    const uint64_t bd = md + (2 + EX) * (PL / 16);
    constexpr int NA = J < 2 ? N1 + NS + N2 : NV;
    scale(pt, &accM[8], rt);
    mbar_wait(sb + B_XA, s & 1);
    wg_fence(); proj_loop<NB, 36, 37>(accB, wr, bd, wl); proj_loop<NB, 0, N1>(accB, wr, bd, wl); wg_commit();
    if (J < 2 && NS > 0) mbar_wait(sb + B_WS, s & 1);
    proj_steps<NB, N1, N1 + NS>(accB, wr, bd, wl);
    mbar_wait(sb + B_XB, (s + 1) & 1);
    if (J < 2 && N2 > 0) mbar_wait(sb + B_W2, s & 1);
    proj_steps<NB, N1 + NS, NA>(accB, wr, bd, wl);
    mbar_wait(sb + B_W3, s & 1);
    if (wg == 0) { TR(2); }
    proj_steps<NB, NA, 36>(accB, wr, bd, wl);
    mbar_wait(sb + B_XT, (s + 1) & 1);
    float4 r0, r1, r2;
    if (RPF > 0) r0 = lds_f4(lnf + 16);
    if (RPF > 1) r1 = lds_f4(lna + 256);
    wg_wait<0>(); pin<NB / 2>(accB);
    if (wg == 0) { TR(3); }
    uint32_t p[16];
    if (RPF < 1) r0 = lds_f4(lnf + 16);
    if (RPF < 2) r1 = lds_f4(lna + 256);
    r2 = lds_f4(lna + 256 + 16);
#pragma unroll
    for (int i = 0; i < 4; i++) p[i] = pt[i];
    scale(&p[4], &accB[0], r0); scale(&p[8], &accB[8], r1); scale(&p[12], &accB[16], r2);
    put(p);
  }
}

template<int J> __device__ __forceinline__ void h_chain(uint8_t* smraw, const uint32_t sb, const int w, int lane, const uint32_t epoch, const bf16* __restrict__ mem0) {
  asm volatile("bar.sync 1, 512;" ::: "memory");
#pragma unroll 1
  for (int i = w * 144 + lane; i < w * 144 + 144; i += 32) {
    const uint4 v = *(const uint4*)(mem0 + (i & 7) * 576 + (i >> 3) * 8);
    *(uint4*)(smraw + H_MEM + i * 16) = v; *(uint4*)(smraw + H_MEM + PL + i * 16) = v;
  }
  *(uint4*)(smraw + H_ZERO + (w * 32 + lane) * 16) = make_uint4(0, 0, 0, 0);
  for (int i = w * 32 + lane; i < 160; i += 128) *(uint4*)(smraw + H_MEM + (i >> 4) * PL + PG + (i & 15) * 16) = make_uint4(0, 0, 0, 0);
  asm volatile("bar.sync 2, 128;" ::: "memory");
  fence_async();
  __syncwarp();
  if (lane == 0) mbar_arrive(sb + B_MEM + w * 8);
  cluster_sync();
  const uint32_t so = sb & 0x1FFFFFF;
  uint32_t ring = (epoch * (NSTEP - 1)) & 3;
  for (int s = 0;; s++) {
    const uint32_t par = s & 1;
    lane = lane_id();
    const float cs = 0.08838834764831845f * 1.4426950408889634f;
    const uint32_t wb = sb + H_WO + w * 48 + lane * 400;
    uint32_t bq[4][12];
    if (J < 2) {
      float sc[20];
      uint32_t pa[12];
      asm volatile("ld.shared.v2.b32 {%0,%1}, [%2];" : "=r"(pa[10]), "=r"(pa[11]) : "r"(sb + H_ZERO));
      const uint64_t qd = mkdesc(sb + H_QB, 128, 2048), kd = mkdesc(sb + H_KB, 128, 2048), vd = mkdesc(sb + H_VB, 2048, 128);
      mbar_wait(sb + B_QK, par);
      TR(8);
      wg_fence();
#pragma unroll
      for (int kk = 0; kk < 8; kk++) { if (kk == 0) ss40tt<0>(sc, qd, kd); else ss40tt<1>(sc, qd + kk * 16, kd + kk * 16); }
      wg_commit();
      if (VW == 0) mbar_wait(sb + B_V, par);
      wg_wait<0>(); pin<20>(sc);
      if (NS > 0 && w == 3 && lane == 0) mbar_arrive(sb + B_WS);
      TR(7);
      float s0 = 0.f, s1 = 0.f;
      if (w < 2) {
        const int r0 = (lane >> 2) * 2 + w - 4 * (lane & 3);
        float m0 = fmaxf(sc[16], sc[17]), m1 = fmaxf(sc[18], sc[19]);
#pragma unroll
        for (int i = 0; i < 4; i += 2) {
          const int c = i >> 1;
          const bool k0 = c > r0, k1 = c + 2 > r0;
          if (k0) { sc[4 * i] = -INFINITY; sc[4 * i + 6] = -INFINITY; }
          if (k1) { sc[4 * i + 1] = -INFINITY; sc[4 * i + 7] = -INFINITY; }
          m0 = fmaxf(m0, fmaxf(sc[4 * i], sc[4 * i + 1]));
          m1 = fmaxf(m1, fmaxf(fmaxf(sc[4 * i + 2], sc[4 * i + 3]), fmaxf(sc[4 * i + 6], sc[4 * i + 7])));
        }
        m1 = fmaxf(m1, __shfl_xor_sync(~0u, m1, 1)); m0 = fmaxf(m0, __shfl_xor_sync(~0u, m0, 1));
        m1 = fmaxf(m1, __shfl_xor_sync(~0u, m1, 2)); m0 = fmaxf(m0, __shfl_xor_sync(~0u, m0, 2));
        m0 *= cs; m1 *= cs;
#pragma unroll
        for (int i = 0; i < 5; i++) {
          if (i & 1) pa[2 * i] = pa[10];
          else {
            const float a = ex2(fmaf(sc[4 * i], cs, -m0)), b = ex2(fmaf(sc[4 * i + 1], cs, -m0));
            s0 += a + b; pa[2 * i] = pk(a, b);
          }
          const float a = ex2(fmaf(sc[4 * i + 2], cs, -m1)), b = ex2(fmaf(sc[4 * i + 3], cs, -m1));
          s1 += a + b; pa[2 * i + 1] = pk(a, b);
        }
      } else {
        float m0 = fmaxf(fmaxf(fmaxf(sc[0], sc[1]), fmaxf(sc[4], sc[5])), fmaxf(fmaxf(fmaxf(sc[8], sc[9]), fmaxf(sc[12], sc[13])), fmaxf(sc[16], sc[17])));
        m0 = fmaxf(m0, __shfl_xor_sync(~0u, m0, 1));
        m0 = fmaxf(m0, __shfl_xor_sync(~0u, m0, 2));
        m0 *= cs;
#pragma unroll
        for (int i = 0; i < 5; i++) {
          const float a = ex2(fmaf(sc[4 * i], cs, -m0)), b = ex2(fmaf(sc[4 * i + 1], cs, -m0));
          s0 += a + b; pa[2 * i] = pk(a, b); pa[2 * i + 1] = pa[10];
        }
        if (VW == 1) mbar_wait(sb + B_V, par);
      }
      TR(4);
      float o[2][32];
      wg_fence();
      rs64<0>(o[0], pa, vd); rs64<1>(o[0], pa + 4, vd + 256); rs64<1>(o[0], pa + 8, vd + 512); wg_commit();
      rs64<0>(o[1], pa, vd + 64); rs64<1>(o[1], pa + 4, vd + 64 + 256); rs64<1>(o[1], pa + 8, vd + 64 + 512); wg_commit();
      s0 += __shfl_xor_sync(~0u, s0, 1); s1 += __shfl_xor_sync(~0u, s1, 1);
      s0 += __shfl_xor_sync(~0u, s0, 2); s1 += __shfl_xor_sync(~0u, s1, 2);
      s0 = rcp(s0); s1 = rcp(s1);
      if (w == 2 && s < NSTEP - 1) {
        const uint32_t omo = so + H_OM + J * 2048 + (lane & 3) * 128 + (((lane >> 2) ^ ((lane & 3) * 2)) * 16);
        constexpr uint32_t R1 = (uint32_t)(1 - J) << 25, R2 = 2u << 25, RL = (uint32_t)J << 25;
        uint32_t x[16];
#pragma unroll
        for (int hf = 0; hf < 2; hf++) {
          if (hf == 0) wg_wait<1>(); else wg_wait<0>();
          pin<32>(o[hf]);
#pragma unroll
          for (int jg = 2 * hf; jg < 2 * hf + 2; jg++) {
#pragma unroll
            for (int i = 0; i < 4; i++) x[4 * jg + i] = pk(o[hf][(jg & 1) * 16 + 4 * i] * s0, o[hf][(jg & 1) * 16 + 4 * i + 1] * s0);
            st_async4(omo + jg * 512 + R1, x[4 * jg], x[4 * jg + 1], x[4 * jg + 2], x[4 * jg + 3], so + B_OM + R1);
            st_async4(omo + jg * 512 + R2, x[4 * jg], x[4 * jg + 1], x[4 * jg + 2], x[4 * jg + 3], so + B_OM + R2);
          }
        }
#pragma unroll
        for (int jg = 0; jg < 4; jg++) sts4(omo + jg * 512 + RL, x[4 * jg], x[4 * jg + 1], x[4 * jg + 2], x[4 * jg + 3]);
        __syncwarp();
        if (lane == 0) { mbar_arrive(sb + B_OM); if (N2 > 0) mbar_arrive(sb + B_W2); }
        TRW(9, 2);
      } else {
        wg_wait<0>();
        pin<32>(o[0]); pin<32>(o[1]);
        if (w < 2) {
          const uint32_t os = sb + H_OS + w * 4096 + lane * 16;
          const uint32_t otag = ORING == NSEG ? (epoch + 1) & 1 : (((uint32_t)(s - J * LAG) / ORING) + 1) & 1;
#pragma unroll
          for (int kk = 0; kk < 8; kk++) {
            const float* oo = &o[kk >> 2][(kk & 3) * 8];
            sts4(os + kk * 512, pk_tag(oo[0] * s0, oo[1] * s0, otag), pk(oo[2] * s1, oo[3] * s1), pk(oo[4] * s0, oo[5] * s0), pk(oo[6] * s1, oo[7] * s1));
          }
        }
      }
    }
#pragma unroll
    for (int u = 0; u < 4; u++)
#pragma unroll
      for (int tt = 0; tt < 3; tt++) ldsm4t(&bq[u][tt * 4], wb + tt * 16 + u * 12800);
    const bool u0 = s < NSEG - 1, u1 = s >= LAG;
    uint4* const gacc = &g_acc[0][0] + ring * 1536;
    if (s < NSTEP - 1) {
      uint4* const pacc = gacc + ((w >> 1) * 384 + J * 64 + (w & 1) * 32 + lane);
      const uint32_t oa = sb + H_OM + ((lane >> 3) & 1) * 2048 + (lane >> 4) * 128 + (((lane & 7) ^ ((lane >> 4) * 2)) * 16);
      mbar_wait(sb + B_OM, par);
      TR(10);
      uint32_t A[8][4];
#pragma unroll
      for (int kk = 0; kk < 8; kk++) ldsm4(A[kk], (oa ^ ((kk & 1) * 64)) + kk * 256);
#pragma unroll
      for (int a = 0; a < 2; a++) {
        float d[3][4];
#pragma unroll
        for (int tt = 0; tt < 3; tt++) { d[tt][0] = d[tt][1] = d[tt][2] = d[tt][3] = 0.f; }
#pragma unroll
        for (int jg = 0; jg < 4; jg++) {
          uint32_t* b = bq[jg];
#pragma unroll
          for (int tt = 0; tt < 3; tt++) HMMA(d[tt], A[2 * jg][0], A[2 * jg][1], A[2 * jg][2], A[2 * jg][3], b[tt * 4], b[tt * 4 + 1]);
          if (a == 0 && jg > 0) {
#pragma unroll
            for (int tt = 0; tt < 3; tt++) ldsm4t(&bq[jg - 1][tt * 4], wb + 192 + tt * 16 + (jg - 1) * 12800);
          }
          if (a == 1 && jg == 0) {
#pragma unroll
            for (int tt = 0; tt < 3; tt++) ldsm4t(&bq[3][tt * 4], wb + 192 + tt * 16 + 3 * 12800);
          }
#pragma unroll
          for (int tt = 0; tt < 3; tt++) HMMA(d[tt], A[2 * jg + 1][0], A[2 * jg + 1][1], A[2 * jg + 1][2], A[2 * jg + 1][3], b[tt * 4 + 2], b[tt * 4 + 3]);
        }
        red4(pacc + a * 768, pk(d[0][0], d[0][1]), pk(d[1][0], d[1][1]), pk(d[2][0], d[2][1]), u0);
        red4(pacc + a * 768 + 192, pk(d[0][2], d[0][3]), pk(d[1][2], d[1][3]), pk(d[2][2], d[2][3]), u1);
      }
      if (lane == 0) mbar_arrive(sb + B_W3);
    }
    const uint32_t c0 = clock();
    TR(11);
    if (J < 2 && w < 2) { fence_async(); __syncwarp(); if (lane == 0) mbar_arrive(sb + B_OS); }
    if (s == NSTEP - 1) break;
    {
      const uint32_t ch = w ^ 2, lf = blockIdx.x & 1;
      const uint32_t la = (u0 && u1) ? lf : u1, lb = (u0 && u1) ? 1 - lf : u1;
      const uint4* const pa_ = gacc + (ch * 384 + la * 192 + lane);
      const uint4* const pb_ = gacc + (ch * 384 + lb * 192 + lane);
      const uint32_t ma = sb + H_MEM + la * PL + ch * 2304 + lane * 16, mb = sb + H_MEM + lb * PL + ch * 2304 + lane * 16;
      const uint32_t ma5 = lane < 24 ? ma + 1920 : sb + H_DUMP + (lane & 7) * 16, mb5 = lane < 24 ? mb + 1920 : ma5;
      const uint32_t dl = PD + (J == 2 ? PDJ : 0) + ch * PDS;
      while ((uint32_t)clock() - c0 < dl) {}
      uint32_t v[12][4];
      uint32_t it = 0;
      while (true) {
#pragma unroll
        for (int i = 0; i < 6; i++) { const int ii = (i + 2 * J) % 6; ld_rlx(v[ii], pa_ + ii * 32); ld_rlx(v[6 + ii], pb_ + ii * 32); }
        uint32_t mn = v[0][3];
#pragma unroll
        for (int i = 1; i < 12; i++) mn = min(mn, v[i][3]);
        if (__all_sync(~0u, mn == 0x4200u)) break;
        if (++it > SPIN_MAX) __trap();
      }
      TRW(12, 2);
#pragma unroll
      for (int i = 0; i < 6; i++) stsm4(i < 5 ? ma + i * 384 : ma5, v[i][0], v[i][1], v[i][2], v[i][3]);
#pragma unroll
      for (int i = 0; i < 6; i++) stsm4(i < 5 ? mb + i * 384 : mb5, v[6 + i][0], v[6 + i][1], v[6 + i][2], v[6 + i][3]);
      TRW(15, 2);
      publish(sb + B_MEM + ch * 8, sb + H_ZERO, lane);
    }
    ring = (ring + 1) & 3;
    TRW(14, 2);
  }
}

__device__ __forceinline__ uint32_t x_load(uint32_t sb, uint32_t bar, int L, int s, int p0, int p1, int d0, uint32_t o0, uint32_t o1, uint32_t epoch, uint32_t ln, int lane, float& nm) {
  const int seg = s - L * LAG;
  if ((uint32_t)seg >= (uint32_t)NSEG) return 0;
  if (ln) {
    flag_wait(&g_fXB[L][seg][0], (epoch + 1) * 8);
    asm volatile("fence.proxy.async.global;" ::: "memory");
  }
  if (lane == 0) {
    const uint8_t* src = (const uint8_t*)&g_xb[L][seg][p0 * 576] + o0;
    uint32_t dst = sb + H_MEM + d0 * PL + o0;
#pragma unroll 1
    for (int p = p0; p < p1; p++, src += PG, dst += PL) bulk_g2s(dst, src, o1 - o0, sb + bar);
  }
  if (ln) {
    float m[4], q[4];
#pragma unroll
    for (int c = 0; c < 4; c++) asm volatile("ld.relaxed.gpu.global.v2.f32 {%0,%1}, [%2];" : "=f"(m[c]), "=f"(q[c]) : "l"(&g_stB[L][seg][c][lane]) : "memory");
    nm = -0.25f * ((m[0] + m[1]) + (m[2] + m[3]));
    float v = 0.f;
#pragma unroll
    for (int c = 0; c < 4; c++) v += q[c] + 144.f * (m[c] + nm) * (m[c] + nm);
    sts1(ln + ((lane >> 1) & 3) * 32 + (lane >> 3) * 8 + (lane & 1) * 4, __float_as_uint(rsqrtf(v * (1.f / 576) + 1e-5f)));
  }
  if (o0 == 0 && (lane >> 3) >= p0 && (lane >> 3) < p1) {
    const uint32_t hi = pk(nm, nm);
    asm volatile("st.shared.v2.b32 [%0], {%1,%2};" :: "r"(sb + H_MEM + (d0 - p0 + (lane >> 3)) * PL + PG + (lane & 7) * 16), "r"(hi), "r"(pk(nm - blo(hi), 0.f)) : "memory");
  }
  return (p1 - p0) * (o1 - o0);
}
__device__ __forceinline__ void x_arm(uint32_t sb, uint32_t bar, uint32_t n, int lane) {
  __syncwarp();
  if (drain(sb + H_ZERO) == lane) mbar_expect(sb + bar, n);
}

__device__ __forceinline__ void h_help(const uint32_t sb, const int h, const int j, const int w, const int lane, const uint32_t epoch) {
  asm volatile("bar.sync 1, 512;" ::: "memory");
  cluster_sync();
  if (w == 0) {
    constexpr uint32_t XS = (N1 + NS) * 256;
    float nf, ns;
    x_arm(sb, B_XB, x_load(sb, B_XB, 0, 0, 0, 4, 6, 0, PG, epoch, sb + H_LN, lane, nf), lane);
    x_arm(sb, B_XT, x_load(sb, B_XT, 0, 1, 0, EX, 2, 0, PG, epoch, sb + H_LN + 128, lane, nf), lane);
#pragma unroll 1
    for (int s = 0; s < NSTEP - 1; s++) {
      mbar_wait(sb + B_ST, s & 1);
      uint32_t n = x_load(sb, B_XA, 0, s + 1, EX, 4, 2 + EX, 0, XS, epoch, 0, lane, nf);
      x_arm(sb, B_XA, n + x_load(sb, B_XA, 1, s + 1, 0, 4, 6, 0, XS, epoch, sb + H_LN + 256, lane, ns), lane);
      mbar_wait(sb + B_XC, s & 1);
      n = x_load(sb, B_XB, 0, s + 1, EX, 4, 2 + EX, XS, PG, epoch, 0, lane, nf);
      n += x_load(sb, B_XB, 1, s + 1, 0, 4, 6, XS, PG, epoch, 0, lane, ns);
      if (lane == 0) mbar_expect(sb + B_XB, n);
      mbar_wait(sb + B_MD, s & 1);
      x_arm(sb, B_XT, x_load(sb, B_XT, 0, s + 2, 0, EX, 2, 0, PG, epoch, sb + H_LN + (s & 1) * 128, lane, nf), lane);
    }
  } else if (w == 1) {
    if (lane == 0 && j < 2) {
#pragma unroll 1
      for (int s = 0; s < NSTEP; s++) {
        const int seg = s - j * LAG;
        mbar_wait(sb + B_OS, s & 1);
        mbar_expect(sb + B_QK, 10240);
        if ((uint32_t)seg < (uint32_t)NSEG) {
          if (OD > 0 && s < NSTEP - 1) __nanosleep(OD);
          uint4* po = &g_O[j][seg % ORING][0][8 * h][0];
          asm volatile("cp.async.bulk.global.shared::cta.bulk_group [%0], [%1], 4096;" :: "l"(po), "r"(sb + H_OS) : "memory");
          asm volatile("cp.async.bulk.global.shared::cta.bulk_group [%0], [%1], 4096;" :: "l"(po + 8192), "r"(sb + H_OS + 4096) : "memory");
          asm volatile("cp.async.bulk.commit_group; cp.async.bulk.wait_group.read 0;" ::: "memory");
          mbar_expect(sb + B_V, 10240);
          if (OW) asm volatile("cp.async.bulk.wait_group 0;" ::: "memory");
          asm volatile("st.relaxed.gpu.global.u32 [%0], %1;" :: "l"(&g_fO[j][seg][h]), "r"(epoch + 1) : "memory");
        } else {
          mbar_expect(sb + B_V, 10240);
        }
      }
      asm volatile("cp.async.bulk.wait_group 0;" ::: "memory");
    }
  } else if (w == 2) {
    uint32_t ring = (epoch * (NSTEP - 1) + 3) & 3;
#pragma unroll 1
    for (int s = 0; s < NSTEP - 1; s++) {
      mbar_wait(sb + B_W3, s & 1);
      if (lane == 0) mbar_expect(sb + B_OM, j < 2 ? 2048 : 4096);
      mbar_wait(sb + B_MEM + 24, (s + 1) & 1);
      if (lane < 16) st_rlx(&g_acc[ring][blockIdx.x * 16 + lane], make_uint4(0, 0, 0, 0));
      ring = (ring + 1) & 3;
    }
  } else if (lane == 0) {
    const uint32_t so = sb & 0x1FFFFFF;
#pragma unroll 1
    for (int s = 0; s < NSTEP; s++) {
      mbar_wait(sb + B_ST, s & 1);
      if (j < 2) bulk_s2s(so + ((1 - j) << 25) + (j ? H_KB : H_QB), sb + H_ST, so + ((1 - j) << 25) + B_QK);
      else { bulk_s2s(so + H_VB, sb + H_QB, so + B_V); bulk_s2s(so + (1 << 25) + H_VB, sb + H_KB, so + (1 << 25) + B_V); }
    }
  }
  __syncwarp();
}

__global__ void __cluster_dims__(6, 1, 1) __launch_bounds__(512, 1)
h_kernel(const bf16* __restrict__ Wq, const bf16* __restrict__ Wk, const bf16* __restrict__ Wv, const bf16* __restrict__ Wo, const bf16* __restrict__ mem0,
         const bf16* __restrict__ x, const bf16* __restrict__ wqkv, const bf16* __restrict__ wo) {
  extern __shared__ __align__(1024) uint8_t smraw[];
  const uint32_t sb = smem_u32(smraw);
  const int j = (blockIdx.x % 6) >> 1, h = (blockIdx.x / 6) * 2 + (blockIdx.x & 1);
  const int tid = threadIdx.x, lane = tid & 31, w = __shfl_sync(~0u, (tid >> 5) & 3, 0), wg = __shfl_sync(~0u, tid >> 7, 0);
  asm volatile("griddepcontrol.launch_dependents;");
  const uint32_t epoch = *(volatile uint32_t*)&g_epoch;
  if (tid == 511) { l2_prefetch(wqkv + blockIdx.x * 10368, 20736); l2_prefetch(wo + blockIdx.x * 3456, 6912); }
  const int u = (wg * 4 + w) * 96 + blockIdx.x, useg = u / 18, urb = (u % 18) / 9;
  if (wg < 3) {
    const int cp = u % 9;
    const uint32_t* p0 = (const uint32_t*)(x + (size_t)(useg * 32 + 2 * (lane >> 2) + urb) * 576) + cp * 32 + (lane & 3);
    uint32_t y[4][4];
#pragma unroll
    for (int i = 0; i < 4; i++) { y[i][0] = __ldg(p0 + i * 8); y[i][2] = __ldg(p0 + i * 8 + 4); y[i][1] = __ldg(p0 + i * 8 + 16 * 288); y[i][3] = __ldg(p0 + i * 8 + 16 * 288 + 4); }
#pragma unroll
    for (int i = 0; i < 4; i++) g_xa[0][useg][(urb * 36 + cp * 4 + i) * 32 + lane] = make_uint4(y[i][0], y[i][1], y[i][2], y[i][3]);
    const float4 s0 = row_stats<2>(&y[0]), s1 = row_stats<2>(&y[2]);
    if ((lane & 3) == 0) { *(float4*)&g_stA[0][useg][urb][2 * cp][lane >> 2] = s0; *(float4*)&g_stA[0][useg][urb][2 * cp + 1][lane >> 2] = s1; }
    flag_add(&g_fXA[0][useg][urb][0], lane);
  }
  __syncthreads();
  {
    const bf16* W = (j == 0 ? Wq : j == 1 ? Wk : Wv) + h * 128;
    {
      const int c = tid & 15;
      const bf16* src = W + (size_t)(tid >> 4) * 4096 + c * 8;
#pragma unroll 1
      for (int kk = tid >> 4; kk < 576; kk += 32, src += 32 * 4096) {
        cp16(kk < KR * 16 ? sb + kk * 272 + c * 16 : sb + H_WL + c * WLS + (kk - KR * 16) * 16, src);
        asm volatile("cp.async.commit_group; cp.async.wait_group %0;" :: "n"(HP) : "memory");
      }
    }
    if (tid < 384) {
      const int d = tid / 24, n = tid % 24;
      const bf16* Wh = Wo + (size_t)(h * 128 + d) * 576 + (18 * (n / 6) + 6 * j + n % 6) * 8;
      const uint32_t dst = sb + H_WO + (((d >> 1) & 3) * 8 + (d >> 3) * 2 + (d & 1)) * 400 + n * 16;
#pragma unroll 1
      for (int i = 0; i < 8; i++) {
        cp16(dst + ((i >> 1) * 32 + (i & 1) * 4) * 400, Wh + i * 16 * 576);
        asm volatile("cp.async.commit_group; cp.async.wait_group %0;" :: "n"(HP) : "memory");
      }
    }
    if (tid == 0) {
      for (int c = 0; c < 4; c++) mbar_init(sb + B_MEM + c * 8, 1);
      mbar_init(sb + B_XT, 1); mbar_init(sb + B_XA, 1); mbar_init(sb + B_WS, 1); mbar_init(sb + B_XC, 8); mbar_init(sb + B_XB, 1); mbar_init(sb + B_MD, 8); mbar_init(sb + B_ST, 8);
      mbar_init(sb + B_QK, 9); mbar_init(sb + B_V, 1); mbar_init(sb + B_OM, j < 2 ? 2 : 1); mbar_init(sb + B_OS, 2);
      mbar_init(sb + B_W2, 1); mbar_init(sb + B_W3, 4);
      mbar_expect(sb + B_QK, 10240); mbar_expect(sb + B_V, 10240);
      mbar_expect(sb + B_OM, j < 2 ? 2048 : 4096);
      asm volatile("fence.mbarrier_init.release.cluster;" ::: "memory");
    }
    cp_wait_all();
    fence_async();
    __syncthreads();
  }
  if (wg < 2) {
    asm volatile("setmaxnreg.inc.sync.aligned.u32 192;");
    if (j == 0) h_proj<0>(sb, wg, w, lane); else if (j == 1) h_proj<1>(sb, wg, w, lane); else h_proj<2>(sb, wg, w, lane);
    cluster_sync();
  } else if (wg == 2) {
    asm volatile("setmaxnreg.dec.sync.aligned.u32 104;");
    if (j == 0) h_chain<0>(smraw, sb, w, lane, epoch, mem0); else if (j == 1) h_chain<1>(smraw, sb, w, lane, epoch, mem0); else h_chain<2>(smraw, sb, w, lane, epoch, mem0);
    cluster_sync();
  } else {
    asm volatile("setmaxnreg.dec.sync.aligned.u32 24;");
    h_help(sb, h, j, w, lane, epoch);
    cluster_sync();
  }
}

#define XA_ON true
constexpr int G_W = 21, G_AQ = 11, G_AO = 4;
constexpr uint32_t G_SMEM = 232448;

template<int N, int NK, bool TWO, class F, class F2, class F3> __device__ __forceinline__ uint32_t gemm_rs(float* acc, const uint4* pa, uint32_t baddr, uint32_t tag, F&& ready, F2&& mid, F3&& late) {
  constexpr int B1 = 6, B3 = 24, B2 = NK - B3;
  uint32_t a[B3 * 4];
  constexpr int KS = N == 168 ? N * 2 : 384;
  const uint64_t bd = N == 168 ? mkdesc(baddr, N * 16, 128) : mkdesc(baddr, 1024, 3072) | (1ull << 62);
  uint32_t bad = 0;
  auto steps = [&](int k0, int k1) {
#pragma unroll
    for (int kk = k0; kk < k1; kk++) {
      const int slot = kk % B3;
      if (N == 192) { if (kk == 0) rs192t<0>(acc, &a[0], bd); else rs192t<1>(acc, &a[slot * 4], bd + kk * KS); }
      if (N == 168) { if (kk == 0) rs168t<0>(acc, &a[0], bd); else rs168t<1>(acc, &a[slot * 4], bd + kk * KS); }
      if (N == 144) rs144t<1>(acc, &a[slot * 4], bd + kk * KS);
    }
    wg_commit();
  };
  auto check = [&](int s0, int s1) {
#pragma unroll
    for (int i = s0; i < s1; i++) {
      asm volatile("lop3.b32 %0, %0, %1, %2, 0xF6;" : "+r"(bad) : "r"(a[i * 4]), "r"(tag));
      if (TWO) asm volatile("lop3.b32 %0, %0, %1, %2, 0xF6;" : "+r"(bad) : "r"(a[i * 4 + 2]), "r"(tag));
    }
  };
#pragma unroll
  for (int i = 0; i < B3; i++) ld_rlx(&a[i * 4], pa + i * 32);
  ready();
  auto refill = [&](int s0, int s1) {
    check(s0, s1);
    pa -= bad & (tag >> 2);
#pragma unroll
    for (int i = s0; i < s1; i++) ld_rlx(&a[i * 4], pa + (B3 + i) * 32);
    asm volatile("{.reg .pred p; setp.eq.u32 p, %0, 77; @p bar.sync 15, 32;}" :: "r"((uint32_t)(size_t)pa) : "memory");
  };
  wg_fence(); steps(0, B1);
  wg_fence(); steps(B1, B1 + GQ);
  wg_wait<1>(); refill(0, B1);
  wg_fence(); steps(B1 + GQ, B2);
  wg_fence(); steps(B2, B2 + GQ);
  wg_wait<1>(); refill(B1, B2);
  wg_fence(); steps(B2 + GQ, B3);
  wg_fence(); steps(B3, B3 + GQ);
  wg_wait<1>();
  check(B2, B3);
  mid(bad & (tag >> 2));
  wg_fence(); steps(B3 + GQ, NK);
  late();
  wg_wait<0>();
  pin<N / 2>(acc);
  check(0, NK == 37 ? 34 - B3 : NK - B3);
  if (NK == 37 && !(tag & 2)) check(34 - B3, 37 - B3);
  return bad;
}
__device__ __forceinline__ void turn_wait(int wg, bool on, int id = 2) { asm volatile("{.reg .pred p; setp.ne.u32 p, %1, 0; @p bar.sync %0, 256;}" :: "r"(id + wg), "r"((uint32_t)on) : "memory"); }
__device__ __forceinline__ void turn_pass(int wg, bool on, int id = 2) { asm volatile("{.reg .pred p; setp.ne.u32 p, %1, 0; @p bar.arrive %0, 256;}" :: "r"(id + 1 - wg), "r"((uint32_t)on) : "memory"); }
__device__ __forceinline__ bool wg_any(bool p, int wg) {
  uint32_t r;
  asm volatile("{.reg .pred p, q; setp.ne.u32 p, %1, 0; bar.red.or.pred q, %2, 128, p; selp.u32 %0, 1, 0, q;}" : "=r"(r) : "r"((uint32_t)p), "r"(6 + wg) : "memory");
  return r;
}

template<int NC> __device__ __forceinline__ void load_b(uint32_t sb, const bf16* __restrict__ src, int nrow) {
  constexpr int RP = 256 / NC;
  const int c = threadIdx.x % NC, r0 = threadIdx.x / NC;
  if (r0 < RP) {
    const bf16* p = src + r0 * 576 + c * 8;
#pragma unroll 2
    for (int r = r0; r < nrow; r += RP, p += RP * 576) cp16(sb + (r >> 3) * 3072 + (c >> 3) * 1024 + (r & 7) * 128 + ((c ^ r) & 7) * 16, p);
  }
}

__device__ __forceinline__ void role_W(uint32_t sb, int c, uint32_t epoch, const bf16* __restrict__ Wo, uint32_t zero) {
  const int tid = threadIdx.x, lane = tid & 31, w = __shfl_sync(~0u, (tid >> 5) & 3, 0), wg = __shfl_sync(~0u, tid >> 7, 0);
  const int ks = c / 3, ns = c % 3, k0 = ks * 37;
  { const uint32_t c0 = clock(); while ((uint32_t)clock() - c0 < WD) {} }
  GT(79, 2);
  {
    const int nblk = min(74, 512 - 2 * k0);
    load_b<24>(sb, Wo + (size_t)k0 * 16 * 576 + ns * 192, nblk * 8);
    for (int i = nblk * 192 + tid; i < 74 * 192; i += 256) sts4(sb + i * 16, 0, 0, 0, 0);
    cp_wait_all();
  }
  fence_async();
  asm volatile("bar.sync 1, 256;" ::: "memory");
  GT(79, 0);
  const int L = w >> 1, rb = w & 1;
#pragma unroll 1
  for (int s = wg; s < NSTEP; s += 2) {
    const int seg = s - L * LAG;
    const bool on = (uint32_t)seg < (uint32_t)NSEG;
    float acc[96];
    if (on) hint_wait(&g_fO[L][seg][min((k0 >> 3) + min(lane, 5), min((k0 + 36) >> 3, 31))], epoch + 1);
    GT(s, 0);
    const uint32_t tag = PRING == NSEG ? (epoch + 1) & 1 : ((seg / PRING) + 1) & 1;
    {
      uint32_t bad, it = 0;
      do {
        bad = gemm_rs<192, 37, false>(acc, &g_O[0][0][0][0][0] + (uint32_t)((((L * ORING + (seg & (ORING - 1))) * 2 + rb) * 256 + k0) * 32 + lane), sb, tag | (ks == 6 ? 2 : 0) | zero, [&] { turn_wait(wg, s > 0 && it == 0); }, [](uint32_t) {}, [] {});
        if (++it > 100000) __trap();
      } while (XA_ON && wg_any(on && (bad & 1), wg));
      turn_pass(wg, s < NSTEP - 1);
      REDO(0);
    }
    GT(s, 1);
    if (on) {
      if (L) __nanosleep(PSD);
      uint4* const pp = &g_P[L][seg & (PRING - 1)][ks][rb][ns * 12][lane];
#pragma unroll
      for (int i = 0; i < 12; i++)
        st_rlx(pp + i * 32, make_uint4(pk_tag(acc[8 * i], acc[8 * i + 1], tag), pk(acc[8 * i + 2], acc[8 * i + 3]), pk(acc[8 * i + 4], acc[8 * i + 5]), pk(acc[8 * i + 6], acc[8 * i + 7])));
      hint_add(&g_fP[L][seg][rb][ns][0], lane);
    }
  }
}

__device__ __forceinline__ void role_R(uint32_t xch, int b, uint32_t epoch, bf16* __restrict__ out) {
  const int lane = threadIdx.x & 31, w = __shfl_sync(~0u, (threadIdx.x >> 5) & 3, 0);
  const int L = b >= 18, cg = b - 18 * L, rb = w >> 1, kk = 2 * cg + (w & 1);
#pragma unroll 1
  for (int seg = 0; seg < NSEG; seg++) {
    const uint32_t tag = PRING == NSEG ? (epoch + 1) & 1 : ((seg / PRING) + 1) & 1;
    uint32_t v[8][4];
    if (XA_ON) flag_wait(&g_fXB[L][seg][0], (epoch + 1) * 8);
    const uint32_t* pr = (const uint32_t*)&g_xb[L][seg][0] + (rb * 144 + kk * 2) * 32 + lane;
#pragma unroll
    for (int i = 0; i < 4; i++) asm volatile("ld.relaxed.gpu.global.u32 %0, [%1];" : "=r"(v[7][i]) : "l"(pr + (i & 1) * 2304 + (i >> 1) * 32) : "memory");
    const uint4* const pp = &g_P[L][seg & (PRING - 1)][0][rb][kk][lane];
    hint_wait(&g_fP[L][seg][rb][cg / 6][0], (epoch + 1) * 7);
    uint32_t it = 0;
    while (true) {
      uint32_t bad = 0;
#pragma unroll
      for (int k = 0; k < 7; k++) ld_rlx(v[k], pp + k * 2304);
#pragma unroll
      for (int k = 0; k < 7; k++) bad |= v[k][0] ^ tag;
      it++;
      if (__all_sync(~0u, (bad & 1) == 0)) break;
      if (it > SPIN_MAX) __trap();
    }
    REDO(3);
    if (L == 0) { GTR(seg, 2); }
    uint32_t y[1][4];
#pragma unroll
    for (int r = 0; r < 4; r++) {
      const float lo = ((blo(v[0][r]) + blo(v[1][r])) + (blo(v[2][r]) + blo(v[3][r]))) + ((blo(v[4][r]) + blo(v[5][r])) + (blo(v[6][r]) + blo(v[7][r])));
      const float hi = ((bhi(v[0][r]) + bhi(v[1][r])) + (bhi(v[2][r]) + bhi(v[3][r]))) + ((bhi(v[4][r]) + bhi(v[5][r])) + (bhi(v[6][r]) + bhi(v[7][r])));
      y[0][r] = (r == 0 && L == 0) ? pk_tag(lo, hi, (epoch + 1) & 1) : pk(lo, hi);
    }
    if (L == 0) {
      st_rlx(&g_xa[1][seg][(rb * 36 + kk) * 32 + lane], make_uint4(y[0][0], y[0][1], y[0][2], y[0][3]));
      const float4 a = row_stats<1>(y);
      const uint32_t xa = xch + ((seg & 1) * 2 + rb) * 128 + (lane >> 2) * 16;
      if ((w & 1) && (lane & 3) == 0) sts4(xa, __float_as_uint(a.x), __float_as_uint(a.y), __float_as_uint(a.z), __float_as_uint(a.w));
      asm volatile("bar.sync %0, 64;" :: "r"(10 + rb) : "memory");
      if (!(w & 1)) {
        float4 o;
        asm volatile("ld.shared.v4.f32 {%0,%1,%2,%3}, [%4];" : "=f"(o.x), "=f"(o.y), "=f"(o.z), "=f"(o.w) : "r"(xa) : "memory");
        const float q0 = a.y + o.y + 8.f * (a.x - o.x) * (a.x - o.x), q1 = a.w + o.w + 8.f * (a.z - o.z) * (a.z - o.z);
        if ((lane & 3) == 0)
          st_rlx(&g_stA[1][seg][rb][cg][lane >> 2], make_uint4(__float_as_uint(0.5f * (a.x + o.x)), (__float_as_uint(q0) & ~1u) | ((epoch + 1) & 1), __float_as_uint(0.5f * (a.z + o.z)), __float_as_uint(q1)));
        hint_add(&g_fXA[1][seg][rb][0], lane);
      }
    } else {
      uint32_t* po = (uint32_t*)(out + (size_t)(seg * 32 + 2 * (lane >> 2) + rb) * 576) + kk * 8 + (lane & 3);
      po[0] = y[0][0]; po[4] = y[0][2]; po[16 * 288] = y[0][1]; po[16 * 288 + 4] = y[0][3];
    }
    GTR(seg, 3);
  }
  if (b == 18 && threadIdx.x == 256) g_epoch = epoch + 1;
}

constexpr uint32_t AQ_KV = 193536, AQ_Q = AQ_KV + 4 * 24 * 304;
__device__ __forceinline__ void role_AQ(uint8_t* smraw, uint32_t sb, int c, uint32_t epoch, const bf16* __restrict__ wqkv, uint32_t zero) {
  const int tid = threadIdx.x, lane = tid & 31, w = __shfl_sync(~0u, (tid >> 5) & 3, 0), wg = __shfl_sync(~0u, tid >> 7, 0);
  {
    if (tid < 240) {
      const int n = tid % 24;
      const bf16* p = wqkv + (size_t)(tid / 24) * 1728 + (n >> 3) * 576 + min(((54 * c) & ~7) + (n & 7) * 8, 568);
#pragma unroll 2
      for (int r = tid / 24; r < 576; r += 10, p += 10 * 1728) cp16(sb + r * 400 + n * 16, p);
    }
    for (int i = tid; i < 1152; i += 256) st_rlx(&g_ones[i], make_uint4(0x3F803F80u, 0x3F803F80u, 0x3F803F80u, 0x3F803F80u));
    cp_wait_all();
    asm volatile("bar.sync 1, 256;" ::: "memory");
    GT(79, 2);
    uint32_t ra = sb + (tid >> 5) * 3200 + (lane >> 2) * 400 + ((lane & 3) + ((27 * c) & 3)) * 4, wa = sb + (tid >> 5) * 2688 + lane * 16;
#pragma unroll 1
    for (int b = 0; b < 9; b++, ra += 8 * 3200, wa += 8 * 2688) {
      uint32_t v[21];
#pragma unroll
      for (int i = 0; i < 21; i++) asm volatile("ld.shared.b32 %0, [%1];" : "=r"(v[i]) : "r"(ra + (i / 7) * 128 + (i % 7) * 16) : "memory");
      asm volatile("bar.sync 1, 256;" ::: "memory");
#pragma unroll
      for (int i = 0; i < 5; i++) stsm4(wa + i * 512, v[4 * i], v[4 * i + 1], v[4 * i + 2], v[4 * i + 3]);
      sts1(wa - lane * 12 + 2560, v[20]);
    }
    for (int i = tid; i < (4 * 24 * 304 + 4 * 16 * 144 + 384) / 16; i += 256) sts4(sb + AQ_KV + i * 16, 0, 0, 0, 0);
  }
  fence_async();
  asm volatile("bar.sync 1, 256;" ::: "memory");
  GT(79, 0);
  const int st = w >> 1, rb = w & 1, g = lane >> 2, q = lane & 3;
  const uint32_t kvb = sb + AQ_KV + w * 24 * 304, qb = sb + AQ_Q + w * 16 * 144;
  const uint32_t rsb = sb + AQ_Q + 4 * 16 * 144 + w * 96;
  const uint32_t tag = (epoch + 1) & 1;
  const uint32_t csa = sb + AQ_KV + 288 + (q >> 1) * 304 + (q & 1) * 8;
#pragma unroll 1
  for (int n = wg; n < NSEG + LEAD; n += 2) {
    const int seg = n - st * LEAD;
    const bool on = (uint32_t)seg < (uint32_t)NSEG;
    float acc[84];
    if (on) { if (st) hint_wait(&g_fXA[1][seg][rb][0], (epoch + 1) * 18); else if (XA_ON) flag_wait(&g_fXA[0][seg][rb][0], (epoch + 1) * 9); }
    GT(n, 0);
    float t0, t1, u0, u1;
    uint4 pv;
    {
      uint32_t bad, it = 0;
      do {
        uint32_t bs = 0;
        uint4 sv[5];
        bad = gemm_rs<168, 36, false>(acc, on ? &g_xa[st][seg][rb * 36 * 32 + lane] : &g_ones[lane], sb, tag | zero, [&] { turn_wait(wg, n > 0 && it == 0); }, [&](uint32_t z) {
          const uint4* ps = &g_stA[st][on ? seg : 0][rb][q][g] + z;
#pragma unroll
          for (int i = 0; i < 4; i++) sv[i] = ld_rlx(ps + i * 32);
          sv[4] = ld_rlx(ps + (q < 2 ? 128 : 0));
          pv = ld_rlx(ps - q * 8);
          asm volatile("{.reg .pred p; setp.eq.u32 p, %0, 77; @p bar.sync 15, 32;}" :: "r"((uint32_t)(size_t)ps) : "memory");
        }, [&] {
          const float p0 = __uint_as_float(pv.x), p1 = __uint_as_float(pv.z);
#pragma unroll
          for (int i = 0; i < 5; i++) bs |= sv[i].y ^ tag;
          bs |= pv.y ^ tag;
          t0 = t1 = u0 = u1 = 0.f;
#pragma unroll
          for (int i = 0; i < 5; i++) if (i < 4 || q < 2) {
            const float d0 = __uint_as_float(sv[i].x) - p0, d1 = __uint_as_float(sv[i].z) - p1;
            t0 += d0; t1 += d1;
            u0 += __uint_as_float(sv[i].y) + 32.f * d0 * d0; u1 += __uint_as_float(sv[i].w) + 32.f * d1 * d1;
          }
          asm volatile("{.reg .pred p; setp.eq.f32 p, %0, %1; @p bar.sync 15, 32;}" :: "f"(u0 + u1), "f"(-1.f) : "memory");
        });
        bad |= bs;
        if (++it > 100000) __trap();
      } while (XA_ON && wg_any(on && st && (bad & 1), wg));
      turn_pass(wg, n >= AQF && n < NSEG + LEAD - 1);
      REDO(1);
    }
    GT(n, 1);
#pragma unroll
    for (int o = 1; o < 4; o *= 2) {
      t0 += __shfl_xor_sync(~0u, t0, o); t1 += __shfl_xor_sync(~0u, t1, o);
      u0 += __shfl_xor_sync(~0u, u0, o); u1 += __shfl_xor_sync(~0u, u1, o);
    }
    t0 *= (1.f / 18); t1 *= (1.f / 18);
    const float mean0 = -(__uint_as_float(pv.x) + t0), mean1 = -(__uint_as_float(pv.z) + t1);
    const float rs0 = rsqrtf(fmaxf(u0 * (1.f / 576) - t0 * t0, 0.f) + 1e-5f), rs1 = rsqrtf(fmaxf(u1 * (1.f / 576) - t1 * t1, 0.f) + 1e-5f);
    if (n == 0) {
      if (w == 2 && g == 0) {
#pragma unroll
        for (int jn = 0; jn < 21; jn++) asm volatile("st.shared.v2.f32 [%0], {%1,%2};" :: "r"(csa + jn * 608), "f"(acc[4 * jn]), "f"(acc[4 * jn + 1]) : "memory");
      }
      asm volatile("bar.sync 4, 128;" ::: "memory");
    }
    if (AQF < NSEG + LEAD) turn_wait(wg, n > 0, 8);
    uint32_t ow[3][3][2];
    if (on) {
      const uint32_t pos0 = (2 * n) % 3, pos1 = (2 * n + 1) % 3, pos2 = (2 * n + 2) % 3;
      const uint32_t aq = qb + g * 144 + 4 * q, alo = kvb + (pos1 * 8 + g) * 304 + 4 * q, ahi = kvb + (pos2 * 8 + g) * 304 + 4 * q;
      const uint32_t e2 = q >= 1 ? 12 : 0, e4 = q >= 2 ? 12 : 0;
      float cs_[21][2];
#pragma unroll
      for (int jn = 0; jn < 21; jn++) asm volatile("ld.shared.v2.f32 {%0,%1}, [%2];" : "=f"(cs_[jn][0]), "=f"(cs_[jn][1]) : "r"(csa + jn * 608));
      if (q < 2) sts1(rsb + (q ? pos2 : pos1) * 32 + g * 4, __float_as_uint(q ? rs1 : rs0));
#pragma unroll
      for (int jn = 0; jn < 21; jn++) {
        const int part = jn / 7, b7 = jn % 7;
        const uint32_t co = 16 * b7 + (b7 > 2 ? 12 : 0) + (b7 > 4 ? 12 : 0), ex = b7 == 2 ? e2 : b7 == 4 ? e4 : 0;
        const uint32_t lo = (part == 0 ? aq : alo + (part - 1) * 144) + co + ex;
        const uint32_t hi = (part == 0 ? aq + 8 * 144 : ahi + (part - 1) * 144) + co + ex;
        const float c0 = cs_[jn][0], c1 = cs_[jn][1];
        if (b7 < 6 || q < 3) {
          sts1(lo, pk(fmaf(mean0, c0, acc[4 * jn]), fmaf(mean0, c1, acc[4 * jn + 1])));
          sts1(hi, pk(fmaf(mean1, c0, acc[4 * jn + 2]), fmaf(mean1, c1, acc[4 * jn + 3])));
        }
      }
      __syncwarp();
      const bool e0 = 2 * q <= g, e1 = 2 * q + 1 <= g;
      float ra0, ra1, rb0, rb1;
      asm volatile("ld.shared.f32 %0, [%1];" : "=f"(ra0) : "r"(rsb + (e0 ? pos1 : pos0) * 32 + q * 8) : "memory");
      asm volatile("ld.shared.f32 %0, [%1];" : "=f"(ra1) : "r"(rsb + (e1 ? pos1 : pos0) * 32 + q * 8 + 4) : "memory");
      asm volatile("ld.shared.f32 %0, [%1];" : "=f"(rb0) : "r"(rsb + (e0 ? pos2 : pos1) * 32 + q * 8) : "memory");
      asm volatile("ld.shared.f32 %0, [%1];" : "=f"(rb1) : "r"(rsb + (e1 ? pos2 : pos1) * 32 + q * 8 + 4) : "memory");
      const float cs = 0.23570226039551584f * 1.4426950408889634f;
      const float fa0 = ra0 * rs0 * cs, fa1 = ra1 * rs0 * cs, fb0 = rb0 * rs1 * cs, fb1 = rb1 * rs1 * cs;
      const float na0 = (e0 || seg > 0) ? 0.f : -INFINITY, na1 = (e1 || seg > 0) ? 0.f : -INFINITY;
      const uint32_t mk = (e0 ? 0xFFFFu : 0u) | (e1 ? 0xFFFF0000u : 0u);
      const uint32_t ka = kvb + (lane & 7) * 304 + min(lane >> 3, 2) * 16;
      float a0[3], a1[3], b0[3], b1[3];
      uint32_t vf[3][3][4];
#pragma unroll
      for (int lh = 0; lh < 3; lh++) {
        uint32_t qa[4], qc[2], kf[3][4];
        ldsm4(qa, qb + (lane & 15) * 144 + (lane >> 4) * 16 + lh * 48);
        ldsm2(qc, qb + (lane & 15) * 144 + 32 + lh * 48);
        ldsm4(kf[0], ka + pos0 * 2432 + lh * 48); ldsm4(kf[1], ka + pos1 * 2432 + lh * 48); ldsm4(kf[2], ka + pos2 * 2432 + lh * 48);
        float sc[3][4];
#pragma unroll
        for (int b = 0; b < 3; b++) {
          sc[b][0] = sc[b][1] = sc[b][2] = sc[b][3] = 0.f;
          HMMA(sc[b], qa[0], qa[1], qa[2], qa[3], kf[b][0], kf[b][1]);
          HMMA8(sc[b], qc[0], qc[1], kf[b][2]);
        }
        a0[lh] = fmaf(e0 ? sc[1][0] : sc[0][0], fa0, na0); a1[lh] = fmaf(e1 ? sc[1][1] : sc[0][1], fa1, na1);
        b0[lh] = (e0 ? sc[2][2] : sc[1][2]) * fb0; b1[lh] = (e1 ? sc[2][3] : sc[1][3]) * fb1;
      }
#pragma unroll
      for (int lh = 0; lh < 3; lh++) {
        ldsm4t(vf[lh][0], ka + pos0 * 2432 + 144 + lh * 48); ldsm4t(vf[lh][1], ka + pos1 * 2432 + 144 + lh * 48); ldsm4t(vf[lh][2], ka + pos2 * 2432 + 144 + lh * 48);
      }
      float m0[3], m1[3];
#pragma unroll
      for (int lh = 0; lh < 3; lh++) { m0[lh] = fmaxf(a0[lh], a1[lh]); m1[lh] = fmaxf(b0[lh], b1[lh]); }
#pragma unroll
      for (int o = 1; o < 4; o *= 2)
#pragma unroll
        for (int lh = 0; lh < 3; lh++) { m0[lh] = fmaxf(m0[lh], __shfl_xor_sync(~0u, m0[lh], o)); m1[lh] = fmaxf(m1[lh], __shfl_xor_sync(~0u, m1[lh], o)); }
      float o_[3][3][4];
#pragma unroll
      for (int lh = 0; lh < 3; lh++) {
        a0[lh] = ex2(a0[lh] - m0[lh]); a1[lh] = ex2(a1[lh] - m0[lh]); b0[lh] = ex2(b0[lh] - m1[lh]); b1[lh] = ex2(b1[lh] - m1[lh]);
        m0[lh] = a0[lh] + a1[lh]; m1[lh] = b0[lh] + b1[lh];
        const uint32_t pa = pk(a0[lh] * ra0, a1[lh] * ra1), pb = pk(b0[lh] * rb0, b1[lh] * rb1);
#pragma unroll
        for (int cb = 0; cb < 3; cb++) {
          float* o = o_[lh][cb];
          o[0] = o[1] = o[2] = o[3] = 0.f;
          HMMA(o, pa & ~mk, 0u, pa & mk, pb & ~mk, vf[lh][0][cb], vf[lh][1][cb]);
          HMMA8(o, 0u, pb & mk, vf[lh][2][cb]);
        }
      }
#pragma unroll
      for (int o = 1; o < 4; o *= 2)
#pragma unroll
        for (int lh = 0; lh < 3; lh++) { m0[lh] += __shfl_xor_sync(~0u, m0[lh], o); m1[lh] += __shfl_xor_sync(~0u, m1[lh], o); }
#pragma unroll
      for (int lh = 0; lh < 3; lh++) {
        const float s0 = rcp(m0[lh]), s1 = rcp(m1[lh]);
#pragma unroll
        for (int cb = 0; cb < 3; cb++) { ow[lh][cb][0] = pk_tag(o_[lh][cb][0] * s0, o_[lh][cb][1] * s0, tag); ow[lh][cb][1] = pk(o_[lh][cb][2] * s1, o_[lh][cb][3] * s1); }
      }
    }
    turn_pass(wg, n < AQF && n < NSEG + LEAD - 1);
    if (AQF < NSEG + LEAD) turn_pass(wg, n < NSEG + LEAD - 1, 8);
    if (on) {
      const uint8_t* po = (const uint8_t*)&g_oA[st][seg][rb * 36 * 32 + g * 4];
#pragma unroll
      for (int lh = 0; lh < 3; lh++) {
        const uint32_t col = 54 * c + 18 * lh + 2 * q, o0 = (col >> 4) * 512 + (col & 6) * 8 + (col & 8), o1 = (col & 8) ? o0 + 504 : o0 + 8;
        if (col < 576) {
          asm volatile("st.relaxed.gpu.global.v2.b32 [%0], {%1,%2};" :: "l"(po + o0), "r"(ow[lh][0][0]), "r"(ow[lh][0][1]) : "memory");
          asm volatile("st.relaxed.gpu.global.v2.b32 [%0], {%1,%2};" :: "l"(po + o1), "r"(ow[lh][1][0]), "r"(ow[lh][1][1]) : "memory");
          if (q == 0) asm volatile("st.relaxed.gpu.global.v2.b32 [%0], {%1,%2};" :: "l"(po + o0 + 512), "r"(ow[lh][2][0]), "r"(ow[lh][2][1]) : "memory");
        }
      }
      hint_add(&g_fOA[st][seg][rb][0], lane);
    }
    GT(n, 2);
  }
}

__device__ __forceinline__ void role_AO(uint8_t* smraw, uint32_t sb, int c, uint32_t epoch, const bf16* __restrict__ wo, uint32_t zero) {
  const int tid = threadIdx.x, lane = tid & 31, w = __shfl_sync(~0u, (tid >> 5) & 3, 0), wg = __shfl_sync(~0u, tid >> 7, 0);
  load_b<18>(sb, wo + c * 144, 576);
  cp_wait_all();
  fence_async();
  asm volatile("bar.sync 1, 256;" ::: "memory");
  GT(79, 0);
  const int st = w >> 1, rb = w & 1, g = lane >> 2, q = lane & 3;
  const uint32_t tag = (epoch + 1) & 1;
#pragma unroll 1
  for (int n = wg; n < NSEG + LEAD; n += 2) {
    const int seg = n - st * LEAD;
    const bool on = (uint32_t)seg < (uint32_t)NSEG;
    float acc[72];
    if (on) { if (st) hint_wait(&g_fXA[1][seg][rb][0], (epoch + 1) * 18); else if (XA_ON) flag_wait(&g_fXA[0][seg][rb][0], (epoch + 1) * 9); }
    {
      uint32_t bad, it = 0;
      do {
        uint32_t br = 0;
        {
          uint32_t res[9][4];
#pragma unroll
          for (int i = 0; i < 9; i++) ld_rlx(res[i], &g_xa[st][on ? seg : 0][(rb * 36 + c * 9) * 32 + lane] + i * 32);
#pragma unroll
          for (int i = 0; i < 36; i++) { acc[2 * i] = blo(res[i >> 2][i & 3]); acc[2 * i + 1] = bhi(res[i >> 2][i & 3]); }
#pragma unroll
          for (int i = 0; i < 9; i++) br |= res[i][0] ^ tag;
          pin<72>(acc); OPAQUE(br);
        }
        if (on) hint_wait(&g_fOA[st][seg][rb][0], (epoch + 1) * G_AQ);
        GT(n, 0);
        bad = gemm_rs<144, 36, true>(acc, &g_oA[st][on ? seg : 0][rb * 36 * 32 + lane], sb, tag | zero, [&] { turn_wait(wg, n > 0 && it == 0); }, [](uint32_t) {}, [] {});
        if (st) bad |= br;
        if (++it > 100000) __trap();
      } while (wg_any(on && (bad & 1), wg));
      turn_pass(wg, n < NSEG + LEAD - 1);
      REDO(2);
    }
    GT(n, 1);
    if (on) {
      uint32_t y[9][4];
      uint32_t* px = (uint32_t*)&g_xb[st][seg][0] + (rb * 144 + c * 18) * 32 + lane;
#pragma unroll
      for (int i = 0; i < 36; i++) {
        y[i >> 2][i & 3] = pk(acc[2 * i], acc[2 * i + 1]);
        px[(i >> 1) * 32 + (i & 1) * 2304] = y[i >> 2][i & 3];
      }
      const float4 a = row_stats<9>(y);
      if (q < 2) g_stB[st][seg][c][rb * 16 + q * 8 + g] = q ? make_float2(a.z, a.w) : make_float2(a.x, a.y);
      flag_add(&g_fXB[st][seg][0], lane);
    }
    GT(n, 2);
  }
}

__global__ void __launch_bounds__(384, 1)
g_kernel(const bf16* __restrict__ wqkv, const bf16* __restrict__ wo, const bf16* __restrict__ Wo, bf16* __restrict__ out, uint32_t zero) {
  extern __shared__ __align__(1024) uint8_t smraw[];
  const uint32_t sb = smem_u32(smraw);
  const uint32_t epoch = *(volatile uint32_t*)&g_epoch;
  const int b = blockIdx.x;
  GT(79, 1);
  if (__shfl_sync(~0u, threadIdx.x >> 8, 0) == 0) {
    asm volatile("setmaxnreg.inc.sync.aligned.u32 224;");
    if (b < G_W) role_W(sb, b, epoch, Wo, zero);
    else if (b < G_W + G_AQ) role_AQ(smraw, sb, b - G_W, epoch, wqkv, zero);
    else role_AO(smraw, sb, b - G_W - G_AQ, epoch, wo, zero);
  } else {
    asm volatile("setmaxnreg.dec.sync.aligned.u32 56;");
    role_R(sb + G_SMEM - 512, b, epoch, out);
  }
}

extern "C" void kernel_launch(void* const* d_in, const int* in_sizes, int n_in, void* d_out, int out_size) {
  const bf16 *x = (const bf16*)d_in[0], *wqkv = (const bf16*)d_in[1], *wo = (const bf16*)d_in[2], *mem0 = (const bf16*)d_in[4];
  const bf16 *Wq = (const bf16*)d_in[5], *Wk = (const bf16*)d_in[6], *Wv = (const bf16*)d_in[7], *Wo = (const bf16*)d_in[8];
  cudaFuncSetAttribute(h_kernel, cudaFuncAttributeMaxDynamicSharedMemorySize, H_SMEM);
  cudaFuncSetAttribute(g_kernel, cudaFuncAttributeMaxDynamicSharedMemorySize, G_SMEM);
  cudaStream_t st = cudaStreamPerThread;
  h_kernel<<<96, 512, H_SMEM, st>>>(Wq, Wk, Wv, Wo, mem0, x, wqkv, wo);
  cudaLaunchConfig_t cfg = {};
  cfg.gridDim = dim3(G_W + G_AQ + G_AO); cfg.blockDim = dim3(384); cfg.dynamicSmemBytes = G_SMEM; cfg.stream = st;
  cudaLaunchAttribute at[1];
  at[0].id = cudaLaunchAttributeProgrammaticStreamSerialization; at[0].val.programmaticStreamSerializationAllowed = 1;
  cfg.attrs = at; cfg.numAttrs = 1;
  cudaLaunchKernelEx(&cfg, g_kernel, wqkv, wo, Wo, (bf16*)d_out, 0u);
}
```

```cpp
#include <cuda_runtime.h>
#include <cuda_bf16.h>
#include <stdint.h>
typedef __nv_bfloat16 bf16;

#define LAG 7
#define EX 2
#define N2 0
#ifndef NV
#define NV 20
#endif
#define PD 600
#define OD 500
#define FM 3
#define PSD 300
#define FB 50
#define PDS 120
#define PC 0
#define ARM 0
#define PDH 100
#define STP 2
#define GP 6000
#define APS 0
#define HD 0
#define PM 200
#define PA 0
#define N1 3
#define NS 4
#define WD 26000
#define HP 6
#define GQ 3
#define KRV 35
#define RPF 3
#define OW 1
#define VW 1
constexpr int NSEG = 64;
constexpr int NSTEP = NSEG + LAG;
constexpr int LEAD = LAG + 1;
constexpr int ORING = 16, PRING = 16;

__device__ uint4 g_xa[2][NSEG][2304];
__device__ uint4 g_stA[2][NSEG][2][18][8];
__device__ uint4 g_oA[2][NSEG][2304];
__device__ uint4 g_xb[2][NSEG][2304];
__device__ float2 g_stB[2][NSEG][4][32];
__device__ uint4 g_O[3][ORING][2][256][32];
__device__ uint4 g_P[2][PRING][7][2][36][32];
__device__ uint4 g_ones[1152];
__device__ __align__(16) uint32_t g_wq[792][672];
__device__ uint32_t g_fWq[11][8];
constexpr int AG = 256;
__device__ __align__(1024) uint4 g_acc[5][48 * AG];
__device__ uint32_t g_fXA[2][NSEG][2][8], g_fP[2][NSEG][2][3][8], g_fOA[2][NSEG][2][8], g_fXB[2][NSEG][8];
__device__ uint32_t g_fO[2][NSEG][32];
__device__ uint32_t g_epoch;
#define TR(i)
#define TRW(i, ww)
#define GT(n, i)
#define GTR(n, i)
#define REDO(i)

#define OPAQUE(x) asm volatile("" : "+r"(x))
template<int N> __device__ __forceinline__ void pin(float* a) {
#pragma unroll
  for (int i = 0; i < N; i++) asm volatile("" : "+f"(a[i]) :: "memory");
}
__device__ __forceinline__ int lane_id() { int l; asm volatile("mov.u32 %0, %%laneid;" : "=r"(l)); return l; }
constexpr uint32_t SPIN_MAX = 4000000;
__device__ __forceinline__ uint32_t smem_u32(const void* p) { return (uint32_t)__cvta_generic_to_shared(p); }
__device__ __forceinline__ void mbar_init(uint32_t mb, uint32_t n) { asm volatile("mbarrier.init.shared::cta.b64 [%0], %1;" :: "r"(mb), "r"(n) : "memory"); }
__device__ __forceinline__ void mbar_expect(uint32_t mb, uint32_t bytes) { asm volatile("mbarrier.arrive.expect_tx.shared::cta.b64 _, [%0], %1;" :: "r"(mb), "r"(bytes) : "memory"); }
__device__ __forceinline__ void mbar_arrive(uint32_t mb) { asm volatile("mbarrier.arrive.shared::cta.b64 _, [%0];" :: "r"(mb) : "memory"); }
__device__ __forceinline__ void mbar_wait(uint32_t mb, uint32_t par) {
  asm volatile("{.reg .pred p; .reg .u32 c;\n"
               "mbarrier.try_wait.parity.shared::cta.b64 p, [%0], %1; @p bra.uni D_%=; mov.u32 c, 0;\n"
               "W_%=: mbarrier.try_wait.parity.shared::cta.b64 p, [%0], %1; @p bra.uni D_%=;\n"
               "add.u32 c, c, 1; setp.lt.u32 p, c, 4000000; @p bra.uni W_%=; trap;\n"
               "D_%=: }" :: "r"(mb), "r"(par) : "memory");
}
__device__ __forceinline__ void st_async1(uint32_t a, uint32_t v, uint32_t mb) {
  asm volatile("st.async.weak.shared::cluster.mbarrier::complete_tx::bytes.b32 [%0], %1, [%2];" :: "r"(a), "r"(v), "r"(mb) : "memory");
}
__device__ __forceinline__ void st_async4(uint32_t a, uint32_t x, uint32_t y, uint32_t z, uint32_t w, uint32_t mb) {
  asm volatile("st.async.weak.shared::cluster.mbarrier::complete_tx::bytes.v4.b32 [%0], {%1,%2,%3,%4}, [%5];" :: "r"(a), "r"(x), "r"(y), "r"(z), "r"(w), "r"(mb) : "memory");
}
__device__ __forceinline__ void fence_async() { asm volatile("fence.proxy.async.shared::cta;" ::: "memory"); }
__device__ __forceinline__ uint32_t drain(uint32_t zero_addr) {
  uint32_t x;
  asm volatile("ld.volatile.shared.b32 %0, [%1];" : "=r"(x) : "r"(zero_addr) : "memory");
  return x;
}
__device__ __forceinline__ void arrive_after(uint32_t mb, uint32_t x, int lane) {
  asm volatile("{.reg .pred p; setp.eq.u32 p, %1, %2; @p mbarrier.arrive.shared::cta.b64 _, [%0];}" :: "r"(mb), "r"(x), "r"(lane) : "memory");
}
__device__ __forceinline__ void publish(uint32_t mb, uint32_t zero_addr, int lane) { arrive_after(mb, drain(zero_addr), lane); }
__device__ __forceinline__ float4 lds_f4(uint32_t a) {
  float4 v; asm volatile("ld.shared.v4.f32 {%0,%1,%2,%3}, [%4];" : "=f"(v.x), "=f"(v.y), "=f"(v.z), "=f"(v.w) : "r"(a)); return v;
}
__device__ __forceinline__ void fence_gpu() { asm volatile("fence.acq_rel.gpu;" ::: "memory"); }
__device__ __forceinline__ void wg_fence() { asm volatile("wgmma.fence.sync.aligned;" ::: "memory"); }
__device__ __forceinline__ void wg_commit() { asm volatile("wgmma.commit_group.sync.aligned;" ::: "memory"); }
template<int N> __device__ __forceinline__ void wg_wait() { asm volatile("wgmma.wait_group.sync.aligned %0;" :: "n"(N) : "memory"); }
__device__ __forceinline__ uint32_t pk(float a, float b) { uint32_t r; asm("cvt.rn.bf16x2.f32 %0, %1, %2;" : "=r"(r) : "f"(b), "f"(a)); return r; }
__device__ __forceinline__ uint32_t pk_tag(float a, float b, uint32_t tag) {
  const uint32_t r = __float_as_uint(a) >> 16;
  return __byte_perm(r + ((r ^ tag) & 1), pk(a, b), 0x7610);
}
__device__ __forceinline__ float blo(uint32_t v) { return __uint_as_float(v << 16); }
__device__ __forceinline__ float bhi(uint32_t v) { return __uint_as_float(v & 0xFFFF0000u); }
__device__ __forceinline__ float ex2(float x) { float y; asm("ex2.approx.ftz.f32 %0, %1;" : "=f"(y) : "f"(x)); return y; }
__device__ __forceinline__ float rsq(float x) { float y; asm("rsqrt.approx.ftz.f32 %0, %1;" : "=f"(y) : "f"(x)); return y; }
__device__ __forceinline__ float rcp(float x) { float y; asm("rcp.approx.ftz.f32 %0, %1;" : "=f"(y) : "f"(x)); return y; }
__device__ __forceinline__ uint64_t mkdesc(uint32_t addr, uint32_t lbo, uint32_t sbo) {
  return (uint64_t)((addr & 0x3FFFF) >> 4) | ((uint64_t)(lbo >> 4) << 16) | ((uint64_t)(sbo >> 4) << 32);
}
__device__ __forceinline__ void cp16(uint32_t dst, const void* src) { asm volatile("cp.async.cg.shared.global [%0], [%1], 16;" :: "r"(dst), "l"(src) : "memory"); }
__device__ __forceinline__ void cp4(uint32_t dst, const void* src) { asm volatile("cp.async.ca.shared.global [%0], [%1], 4;" :: "r"(dst), "l"(src) : "memory"); }
__device__ __forceinline__ void cp_wait_all() { asm volatile("cp.async.commit_group; cp.async.wait_group 0;" ::: "memory"); }
__device__ __forceinline__ void ldsm4(uint32_t* r, uint32_t addr) {
  asm volatile("ldmatrix.sync.aligned.m8n8.x4.shared.b16 {%0,%1,%2,%3}, [%4];" : "=r"(r[0]), "=r"(r[1]), "=r"(r[2]), "=r"(r[3]) : "r"(addr) : "memory");
}
__device__ __forceinline__ void ldsm2(uint32_t* r, uint32_t addr) {
  asm volatile("ldmatrix.sync.aligned.m8n8.x2.shared.b16 {%0,%1}, [%2];" : "=r"(r[0]), "=r"(r[1]) : "r"(addr) : "memory");
}
__device__ __forceinline__ void ldsm4t(uint32_t* r, uint32_t addr) {
  asm volatile("ldmatrix.sync.aligned.m8n8.x4.trans.shared.b16 {%0,%1,%2,%3}, [%4];" : "=r"(r[0]), "=r"(r[1]), "=r"(r[2]), "=r"(r[3]) : "r"(addr) : "memory");
}
__device__ __forceinline__ void bulk_g2s(uint32_t dst, const void* src, uint32_t bytes, uint32_t mb) {
  asm volatile("cp.async.bulk.shared::cluster.global.mbarrier::complete_tx::bytes [%0], [%1], %2, [%3];" :: "r"(dst), "l"(src), "r"(bytes), "r"(mb) : "memory");
}
__device__ __forceinline__ void bulk_s2g(void* dst, uint32_t src, uint32_t bytes) {
  asm volatile("cp.async.bulk.global.shared::cta.bulk_group [%0], [%1], %2; cp.async.bulk.commit_group;" :: "l"(dst), "r"(src), "r"(bytes) : "memory");
}
__device__ __forceinline__ void bulk_s2s(uint32_t dst, uint32_t src, uint32_t mb) {
  asm volatile("cp.async.bulk.shared::cluster.shared::cta.mbarrier::complete_tx::bytes [%0], [%1], 8192, [%2];" :: "r"(dst), "r"(src), "r"(mb) : "memory");
}
__device__ __forceinline__ void l2_prefetch(const void* p, uint32_t bytes) { asm volatile("cp.async.bulk.prefetch.L2.global [%0], %1;" :: "l"(p), "r"(bytes) : "memory"); }
__device__ __forceinline__ uint32_t ld_acq(const uint32_t* p) { uint32_t v; asm volatile("ld.acquire.gpu.global.u32 %0, [%1];" : "=r"(v) : "l"(p) : "memory"); return v; }
__device__ __forceinline__ uint4 ld_rlx(const uint4* p) {
  uint4 v; asm volatile("ld.relaxed.gpu.global.v4.b32 {%0,%1,%2,%3}, [%4];" : "=r"(v.x), "=r"(v.y), "=r"(v.z), "=r"(v.w) : "l"(p) : "memory"); return v;
}
__device__ __forceinline__ void ld_rlx(uint32_t* r, const uint4* p) {
  asm volatile("ld.relaxed.gpu.global.v4.b32 {%0,%1,%2,%3}, [%4];" : "=r"(r[0]), "=r"(r[1]), "=r"(r[2]), "=r"(r[3]) : "l"(p) : "memory");
}
__device__ __forceinline__ void st_rlx(uint4* p, uint4 v) {
  asm volatile("st.relaxed.gpu.global.v4.b32 [%0], {%1,%2,%3,%4};" :: "l"(p), "r"(v.x), "r"(v.y), "r"(v.z), "r"(v.w) : "memory");
}
__device__ __forceinline__ void red4(uint4* p, uint32_t a, uint32_t b, uint32_t c, bool on) {
  asm volatile("{.reg .pred p; setp.ne.u32 p, %5, 0; @p red.relaxed.gpu.global.add.noftz.v4.bf16x2 [%0], {%1,%2,%3,%4};}"
               :: "l"(p), "r"(a), "r"(b), "r"(c), "r"(0x3F80u), "r"((uint32_t)on) : "memory");
}
__device__ __forceinline__ void stsm4(uint32_t a, uint32_t x, uint32_t y, uint32_t z, uint32_t w) {
  asm volatile("stmatrix.sync.aligned.m8n8.x4.shared.b16 [%0], {%1,%2,%3,%4};" :: "r"(a), "r"(x), "r"(y), "r"(z), "r"(w) : "memory");
}
__device__ __forceinline__ uint32_t movt(uint32_t v) { uint32_t r; asm volatile("movmatrix.sync.aligned.m8n8.trans.b16 %0, %1;" : "=r"(r) : "r"(v)); return r; }
__device__ __forceinline__ void sts1(uint32_t a, uint32_t v) { asm volatile("st.shared.b32 [%0], %1;" :: "r"(a), "r"(v) : "memory"); }
__device__ __forceinline__ void sts4(uint32_t a, uint32_t x, uint32_t y, uint32_t z, uint32_t w) { asm volatile("st.shared.v4.b32 [%0], {%1,%2,%3,%4};" :: "r"(a), "r"(x), "r"(y), "r"(z), "r"(w) : "memory"); }
__device__ __forceinline__ void hint_add(uint32_t* p, int lane) {
  asm volatile("{.reg .pred p; setp.eq.u32 p, %1, 0; @p red.relaxed.gpu.global.inc.u32 [%0], 0xFFFFFFFF;}" :: "l"(p), "r"(lane) : "memory");
}
__device__ __forceinline__ void hint_wait(const uint32_t* p, uint32_t target) {
  uint32_t it = 0;
  while (true) {
    uint32_t v;
    asm volatile("ld.relaxed.gpu.global.u32 %0, [%1];" : "=r"(v) : "l"(p) : "memory");
    if (__all_sync(~0u, v == target)) break;
    if (FB > 0) __nanosleep(FB);
    if (++it > SPIN_MAX) __trap();
  }
}
__device__ __forceinline__ void flag_wait(const uint32_t* p, uint32_t target) {
  if (!__all_sync(~0u, ld_acq(p) == target)) { hint_wait(p, target); ld_acq(p); }
}
__device__ __forceinline__ void flag_add(uint32_t* p, int lane) {
  fence_gpu();
  __syncwarp();
  hint_add(p, lane);
}
#define HMMA(d, a0, a1, a2, a3, b0, b1) asm volatile("mma.sync.aligned.m16n8k16.row.col.f32.bf16.bf16.f32 {%0,%1,%2,%3},{%4,%5,%6,%7},{%8,%9},{%0,%1,%2,%3};" \
  : "+f"((d)[0]), "+f"((d)[1]), "+f"((d)[2]), "+f"((d)[3]) : "r"(a0), "r"(a1), "r"(a2), "r"(a3), "r"(b0), "r"(b1))
#define HMMA8(d, a0, a1, b0) asm volatile("mma.sync.aligned.m16n8k8.row.col.f32.bf16.bf16.f32 {%0,%1,%2,%3},{%4,%5},{%6},{%0,%1,%2,%3};" \
  : "+f"((d)[0]), "+f"((d)[1]), "+f"((d)[2]), "+f"((d)[3]) : "r"(a0), "r"(a1), "r"(b0))

template<int ACC> __device__ __forceinline__ void rs24(float* d, const uint32_t* a, uint64_t b) {
  if (ACC) asm volatile("wgmma.mma_async.sync.aligned.m64n24k16.f32.bf16.bf16 {%0,%1,%2,%3,%4,%5,%6,%7,%8,%9,%10,%11},{%12,%13,%14,%15},%16,1,1,1,0;"
    : "+f"(d[0]), "+f"(d[1]), "+f"(d[2]), "+f"(d[3]), "+f"(d[4]), "+f"(d[5]), "+f"(d[6]), "+f"(d[7]), "+f"(d[8]), "+f"(d[9]), "+f"(d[10]), "+f"(d[11])
    : "r"(a[0]), "r"(a[1]), "r"(a[2]), "r"(a[3]), "l"(b));
  else asm volatile("wgmma.mma_async.sync.aligned.m64n24k16.f32.bf16.bf16 {%0,%1,%2,%3,%4,%5,%6,%7,%8,%9,%10,%11},{%12,%13,%14,%15},%16,0,1,1,0;"
    : "=f"(d[0]), "=f"(d[1]), "=f"(d[2]), "=f"(d[3]), "=f"(d[4]), "=f"(d[5]), "=f"(d[6]), "=f"(d[7]), "=f"(d[8]), "=f"(d[9]), "=f"(d[10]), "=f"(d[11])
    : "r"(a[0]), "r"(a[1]), "r"(a[2]), "r"(a[3]), "l"(b));
}

template<int ACC> __device__ __forceinline__ void rs32(float* d, const uint32_t* a, uint64_t b) {
  if (ACC) asm volatile("wgmma.mma_async.sync.aligned.m64n32k16.f32.bf16.bf16 {%0,%1,%2,%3,%4,%5,%6,%7,%8,%9,%10,%11,%12,%13,%14,%15},{%16,%17,%18,%19},%20,1,1,1,0;"
    : "+f"(d[0]), "+f"(d[1]), "+f"(d[2]), "+f"(d[3]), "+f"(d[4]), "+f"(d[5]), "+f"(d[6]), "+f"(d[7]), "+f"(d[8]), "+f"(d[9]), "+f"(d[10]), "+f"(d[11]),
      "+f"(d[12]), "+f"(d[13]), "+f"(d[14]), "+f"(d[15])
    : "r"(a[0]), "r"(a[1]), "r"(a[2]), "r"(a[3]), "l"(b));
  else asm volatile("wgmma.mma_async.sync.aligned.m64n32k16.f32.bf16.bf16 {%0,%1,%2,%3,%4,%5,%6,%7,%8,%9,%10,%11,%12,%13,%14,%15},{%16,%17,%18,%19},%20,0,1,1,0;"
    : "=f"(d[0]), "=f"(d[1]), "=f"(d[2]), "=f"(d[3]), "=f"(d[4]), "=f"(d[5]), "=f"(d[6]), "=f"(d[7]), "=f"(d[8]), "=f"(d[9]), "=f"(d[10]), "=f"(d[11]),
      "=f"(d[12]), "=f"(d[13]), "=f"(d[14]), "=f"(d[15])
    : "r"(a[0]), "r"(a[1]), "r"(a[2]), "r"(a[3]), "l"(b));
}

template<int ACC> __device__ __forceinline__ void rs48(float* d, const uint32_t* a, uint64_t b) {
  if (ACC) asm volatile("wgmma.mma_async.sync.aligned.m64n48k16.f32.bf16.bf16 {%0,%1,%2,%3,%4,%5,%6,%7,%8,%9,%10,%11,%12,%13,%14,%15,%16,%17,%18,%19,%20,%21,%22,%23},{%24,%25,%26,%27},%28,1,1,1,0;"
    : "+f"(d[0]), "+f"(d[1]), "+f"(d[2]), "+f"(d[3]), "+f"(d[4]), "+f"(d[5]), "+f"(d[6]), "+f"(d[7]), "+f"(d[8]), "+f"(d[9]), "+f"(d[10]), "+f"(d[11]),
      "+f"(d[12]), "+f"(d[13]), "+f"(d[14]), "+f"(d[15]), "+f"(d[16]), "+f"(d[17]), "+f"(d[18]), "+f"(d[19]), "+f"(d[20]), "+f"(d[21]), "+f"(d[22]), "+f"(d[23])
    : "r"(a[0]), "r"(a[1]), "r"(a[2]), "r"(a[3]), "l"(b));
  else asm volatile("wgmma.mma_async.sync.aligned.m64n48k16.f32.bf16.bf16 {%0,%1,%2,%3,%4,%5,%6,%7,%8,%9,%10,%11,%12,%13,%14,%15,%16,%17,%18,%19,%20,%21,%22,%23},{%24,%25,%26,%27},%28,0,1,1,0;"
    : "=f"(d[0]), "=f"(d[1]), "=f"(d[2]), "=f"(d[3]), "=f"(d[4]), "=f"(d[5]), "=f"(d[6]), "=f"(d[7]), "=f"(d[8]), "=f"(d[9]), "=f"(d[10]), "=f"(d[11]),
      "=f"(d[12]), "=f"(d[13]), "=f"(d[14]), "=f"(d[15]), "=f"(d[16]), "=f"(d[17]), "=f"(d[18]), "=f"(d[19]), "=f"(d[20]), "=f"(d[21]), "=f"(d[22]), "=f"(d[23])
    : "r"(a[0]), "r"(a[1]), "r"(a[2]), "r"(a[3]), "l"(b));
}

template<int ACC> __device__ __forceinline__ void rs56(float* d, const uint32_t* a, uint64_t b) {
  if (ACC) asm volatile("wgmma.mma_async.sync.aligned.m64n56k16.f32.bf16.bf16 {%0,%1,%2,%3,%4,%5,%6,%7,%8,%9,%10,%11,%12,%13,%14,%15,%16,%17,%18,%19,%20,%21,%22,%23,%24,%25,%26,%27},{%28,%29,%30,%31},%32,1,1,1,0;"
    : "+f"(d[0]), "+f"(d[1]), "+f"(d[2]), "+f"(d[3]), "+f"(d[4]), "+f"(d[5]), "+f"(d[6]), "+f"(d[7]), "+f"(d[8]), "+f"(d[9]), "+f"(d[10]), "+f"(d[11]),
      "+f"(d[12]), "+f"(d[13]), "+f"(d[14]), "+f"(d[15]), "+f"(d[16]), "+f"(d[17]), "+f"(d[18]), "+f"(d[19]), "+f"(d[20]), "+f"(d[21]), "+f"(d[22]), "+f"(d[23]),
      "+f"(d[24]), "+f"(d[25]), "+f"(d[26]), "+f"(d[27])
    : "r"(a[0]), "r"(a[1]), "r"(a[2]), "r"(a[3]), "l"(b));
  else asm volatile("wgmma.mma_async.sync.aligned.m64n56k16.f32.bf16.bf16 {%0,%1,%2,%3,%4,%5,%6,%7,%8,%9,%10,%11,%12,%13,%14,%15,%16,%17,%18,%19,%20,%21,%22,%23,%24,%25,%26,%27},{%28,%29,%30,%31},%32,0,1,1,0;"
    : "=f"(d[0]), "=f"(d[1]), "=f"(d[2]), "=f"(d[3]), "=f"(d[4]), "=f"(d[5]), "=f"(d[6]), "=f"(d[7]), "=f"(d[8]), "=f"(d[9]), "=f"(d[10]), "=f"(d[11]),
      "=f"(d[12]), "=f"(d[13]), "=f"(d[14]), "=f"(d[15]), "=f"(d[16]), "=f"(d[17]), "=f"(d[18]), "=f"(d[19]), "=f"(d[20]), "=f"(d[21]), "=f"(d[22]), "=f"(d[23]),
      "=f"(d[24]), "=f"(d[25]), "=f"(d[26]), "=f"(d[27])
    : "r"(a[0]), "r"(a[1]), "r"(a[2]), "r"(a[3]), "l"(b));
}

template<int ACC> __device__ __forceinline__ void rs64(float* d, const uint32_t* a, uint64_t b) {
  if (ACC) asm volatile("wgmma.mma_async.sync.aligned.m64n64k16.f32.bf16.bf16 {%0,%1,%2,%3,%4,%5,%6,%7,%8,%9,%10,%11,%12,%13,%14,%15,%16,%17,%18,%19,%20,%21,%22,%23,%24,%25,%26,%27,%28,%29,%30,%31},{%32,%33,%34,%35},%36,1,1,1,0;"
    : "+f"(d[0]), "+f"(d[1]), "+f"(d[2]), "+f"(d[3]), "+f"(d[4]), "+f"(d[5]), "+f"(d[6]), "+f"(d[7]), "+f"(d[8]), "+f"(d[9]), "+f"(d[10]), "+f"(d[11]),
      "+f"(d[12]), "+f"(d[13]), "+f"(d[14]), "+f"(d[15]), "+f"(d[16]), "+f"(d[17]), "+f"(d[18]), "+f"(d[19]), "+f"(d[20]), "+f"(d[21]), "+f"(d[22]), "+f"(d[23]),
      "+f"(d[24]), "+f"(d[25]), "+f"(d[26]), "+f"(d[27]), "+f"(d[28]), "+f"(d[29]), "+f"(d[30]), "+f"(d[31])
    : "r"(a[0]), "r"(a[1]), "r"(a[2]), "r"(a[3]), "l"(b));
  else asm volatile("wgmma.mma_async.sync.aligned.m64n64k16.f32.bf16.bf16 {%0,%1,%2,%3,%4,%5,%6,%7,%8,%9,%10,%11,%12,%13,%14,%15,%16,%17,%18,%19,%20,%21,%22,%23,%24,%25,%26,%27,%28,%29,%30,%31},{%32,%33,%34,%35},%36,0,1,1,0;"
    : "=f"(d[0]), "=f"(d[1]), "=f"(d[2]), "=f"(d[3]), "=f"(d[4]), "=f"(d[5]), "=f"(d[6]), "=f"(d[7]), "=f"(d[8]), "=f"(d[9]), "=f"(d[10]), "=f"(d[11]),
      "=f"(d[12]), "=f"(d[13]), "=f"(d[14]), "=f"(d[15]), "=f"(d[16]), "=f"(d[17]), "=f"(d[18]), "=f"(d[19]), "=f"(d[20]), "=f"(d[21]), "=f"(d[22]), "=f"(d[23]),
      "=f"(d[24]), "=f"(d[25]), "=f"(d[26]), "=f"(d[27]), "=f"(d[28]), "=f"(d[29]), "=f"(d[30]), "=f"(d[31])
    : "r"(a[0]), "r"(a[1]), "r"(a[2]), "r"(a[3]), "l"(b));
}

template<int ACC> __device__ __forceinline__ void ss24tn(float* d, uint64_t a, uint64_t b) {
  if (ACC) asm volatile("wgmma.mma_async.sync.aligned.m64n24k16.f32.bf16.bf16 {%0,%1,%2,%3,%4,%5,%6,%7,%8,%9,%10,%11},%12,%13,1,1,1,1,0;"
    : "+f"(d[0]), "+f"(d[1]), "+f"(d[2]), "+f"(d[3]), "+f"(d[4]), "+f"(d[5]), "+f"(d[6]), "+f"(d[7]), "+f"(d[8]), "+f"(d[9]), "+f"(d[10]), "+f"(d[11])
    : "l"(a), "l"(b));
  else asm volatile("wgmma.mma_async.sync.aligned.m64n24k16.f32.bf16.bf16 {%0,%1,%2,%3,%4,%5,%6,%7,%8,%9,%10,%11},%12,%13,0,1,1,1,0;"
    : "=f"(d[0]), "=f"(d[1]), "=f"(d[2]), "=f"(d[3]), "=f"(d[4]), "=f"(d[5]), "=f"(d[6]), "=f"(d[7]), "=f"(d[8]), "=f"(d[9]), "=f"(d[10]), "=f"(d[11])
    : "l"(a), "l"(b));
}

template<int ACC> __device__ __forceinline__ void ss32tn(float* d, uint64_t a, uint64_t b) {
  if (ACC) asm volatile("wgmma.mma_async.sync.aligned.m64n32k16.f32.bf16.bf16 {%0,%1,%2,%3,%4,%5,%6,%7,%8,%9,%10,%11,%12,%13,%14,%15},%16,%17,1,1,1,1,0;"
    : "+f"(d[0]), "+f"(d[1]), "+f"(d[2]), "+f"(d[3]), "+f"(d[4]), "+f"(d[5]), "+f"(d[6]), "+f"(d[7]), "+f"(d[8]), "+f"(d[9]), "+f"(d[10]), "+f"(d[11]),
      "+f"(d[12]), "+f"(d[13]), "+f"(d[14]), "+f"(d[15])
    : "l"(a), "l"(b));
  else asm volatile("wgmma.mma_async.sync.aligned.m64n32k16.f32.bf16.bf16 {%0,%1,%2,%3,%4,%5,%6,%7,%8,%9,%10,%11,%12,%13,%14,%15},%16,%17,0,1,1,1,0;"
    : "=f"(d[0]), "=f"(d[1]), "=f"(d[2]), "=f"(d[3]), "=f"(d[4]), "=f"(d[5]), "=f"(d[6]), "=f"(d[7]), "=f"(d[8]), "=f"(d[9]), "=f"(d[10]), "=f"(d[11]),
      "=f"(d[12]), "=f"(d[13]), "=f"(d[14]), "=f"(d[15])
    : "l"(a), "l"(b));
}

template<int ACC> __device__ __forceinline__ void ss48tn(float* d, uint64_t a, uint64_t b) {
  if (ACC) asm volatile("wgmma.mma_async.sync.aligned.m64n48k16.f32.bf16.bf16 {%0,%1,%2,%3,%4,%5,%6,%7,%8,%9,%10,%11,%12,%13,%14,%15,%16,%17,%18,%19,%20,%21,%22,%23},%24,%25,1,1,1,1,0;"
    : "+f"(d[0]), "+f"(d[1]), "+f"(d[2]), "+f"(d[3]), "+f"(d[4]), "+f"(d[5]), "+f"(d[6]), "+f"(d[7]), "+f"(d[8]), "+f"(d[9]), "+f"(d[10]), "+f"(d[11]),
      "+f"(d[12]), "+f"(d[13]), "+f"(d[14]), "+f"(d[15]), "+f"(d[16]), "+f"(d[17]), "+f"(d[18]), "+f"(d[19]), "+f"(d[20]), "+f"(d[21]), "+f"(d[22]), "+f"(d[23])
    : "l"(a), "l"(b));
  else asm volatile("wgmma.mma_async.sync.aligned.m64n48k16.f32.bf16.bf16 {%0,%1,%2,%3,%4,%5,%6,%7,%8,%9,%10,%11,%12,%13,%14,%15,%16,%17,%18,%19,%20,%21,%22,%23},%24,%25,0,1,1,1,0;"
    : "=f"(d[0]), "=f"(d[1]), "=f"(d[2]), "=f"(d[3]), "=f"(d[4]), "=f"(d[5]), "=f"(d[6]), "=f"(d[7]), "=f"(d[8]), "=f"(d[9]), "=f"(d[10]), "=f"(d[11]),
      "=f"(d[12]), "=f"(d[13]), "=f"(d[14]), "=f"(d[15]), "=f"(d[16]), "=f"(d[17]), "=f"(d[18]), "=f"(d[19]), "=f"(d[20]), "=f"(d[21]), "=f"(d[22]), "=f"(d[23])
    : "l"(a), "l"(b));
}

template<int ACC> __device__ __forceinline__ void ss56tn(float* d, uint64_t a, uint64_t b) {
  if (ACC) asm volatile("wgmma.mma_async.sync.aligned.m64n56k16.f32.bf16.bf16 {%0,%1,%2,%3,%4,%5,%6,%7,%8,%9,%10,%11,%12,%13,%14,%15,%16,%17,%18,%19,%20,%21,%22,%23,%24,%25,%26,%27},%28,%29,1,1,1,1,0;"
    : "+f"(d[0]), "+f"(d[1]), "+f"(d[2]), "+f"(d[3]), "+f"(d[4]), "+f"(d[5]), "+f"(d[6]), "+f"(d[7]), "+f"(d[8]), "+f"(d[9]), "+f"(d[10]), "+f"(d[11]),
      "+f"(d[12]), "+f"(d[13]), "+f"(d[14]), "+f"(d[15]), "+f"(d[16]), "+f"(d[17]), "+f"(d[18]), "+f"(d[19]), "+f"(d[20]), "+f"(d[21]), "+f"(d[22]), "+f"(d[23]),
      "+f"(d[24]), "+f"(d[25]), "+f"(d[26]), "+f"(d[27])
    : "l"(a), "l"(b));
  else asm volatile("wgmma.mma_async.sync.aligned.m64n56k16.f32.bf16.bf16 {%0,%1,%2,%3,%4,%5,%6,%7,%8,%9,%10,%11,%12,%13,%14,%15,%16,%17,%18,%19,%20,%21,%22,%23,%24,%25,%26,%27},%28,%29,0,1,1,1,0;"
    : "=f"(d[0]), "=f"(d[1]), "=f"(d[2]), "=f"(d[3]), "=f"(d[4]), "=f"(d[5]), "=f"(d[6]), "=f"(d[7]), "=f"(d[8]), "=f"(d[9]), "=f"(d[10]), "=f"(d[11]),
      "=f"(d[12]), "=f"(d[13]), "=f"(d[14]), "=f"(d[15]), "=f"(d[16]), "=f"(d[17]), "=f"(d[18]), "=f"(d[19]), "=f"(d[20]), "=f"(d[21]), "=f"(d[22]), "=f"(d[23]),
      "=f"(d[24]), "=f"(d[25]), "=f"(d[26]), "=f"(d[27])
    : "l"(a), "l"(b));
}

template<int ACC> __device__ __forceinline__ void ss40tt(float* d, uint64_t a, uint64_t b) {
  if (ACC) asm volatile("wgmma.mma_async.sync.aligned.m64n40k16.f32.bf16.bf16 {%0,%1,%2,%3,%4,%5,%6,%7,%8,%9,%10,%11,%12,%13,%14,%15,%16,%17,%18,%19},%20,%21,1,1,1,1,1;"
    : "+f"(d[0]), "+f"(d[1]), "+f"(d[2]), "+f"(d[3]), "+f"(d[4]), "+f"(d[5]), "+f"(d[6]), "+f"(d[7]), "+f"(d[8]), "+f"(d[9]), "+f"(d[10]), "+f"(d[11]),
      "+f"(d[12]), "+f"(d[13]), "+f"(d[14]), "+f"(d[15]), "+f"(d[16]), "+f"(d[17]), "+f"(d[18]), "+f"(d[19])
    : "l"(a), "l"(b));
  else asm volatile("wgmma.mma_async.sync.aligned.m64n40k16.f32.bf16.bf16 {%0,%1,%2,%3,%4,%5,%6,%7,%8,%9,%10,%11,%12,%13,%14,%15,%16,%17,%18,%19},%20,%21,0,1,1,1,1;"
    : "=f"(d[0]), "=f"(d[1]), "=f"(d[2]), "=f"(d[3]), "=f"(d[4]), "=f"(d[5]), "=f"(d[6]), "=f"(d[7]), "=f"(d[8]), "=f"(d[9]), "=f"(d[10]), "=f"(d[11]),
      "=f"(d[12]), "=f"(d[13]), "=f"(d[14]), "=f"(d[15]), "=f"(d[16]), "=f"(d[17]), "=f"(d[18]), "=f"(d[19])
    : "l"(a), "l"(b));
}

template<int ACC> __device__ __forceinline__ void rs144t(float* d, const uint32_t* a, uint64_t b) {
  if (ACC) asm volatile("wgmma.mma_async.sync.aligned.m64n144k16.f32.bf16.bf16 {%0,%1,%2,%3,%4,%5,%6,%7,%8,%9,%10,%11,%12,%13,%14,%15,%16,%17,%18,%19,%20,%21,%22,%23,%24,%25,%26,%27,%28,%29,%30,%31,%32,%33,%34,%35,%36,%37,%38,%39,%40,%41,%42,%43,%44,%45,%46,%47,%48,%49,%50,%51,%52,%53,%54,%55,%56,%57,%58,%59,%60,%61,%62,%63,%64,%65,%66,%67,%68,%69,%70,%71},{%72,%73,%74,%75},%76,1,1,1,1;"
    : "+f"(d[0]), "+f"(d[1]), "+f"(d[2]), "+f"(d[3]), "+f"(d[4]), "+f"(d[5]), "+f"(d[6]), "+f"(d[7]), "+f"(d[8]), "+f"(d[9]), "+f"(d[10]), "+f"(d[11]),
      "+f"(d[12]), "+f"(d[13]), "+f"(d[14]), "+f"(d[15]), "+f"(d[16]), "+f"(d[17]), "+f"(d[18]), "+f"(d[19]), "+f"(d[20]), "+f"(d[21]), "+f"(d[22]), "+f"(d[23]),
      "+f"(d[24]), "+f"(d[25]), "+f"(d[26]), "+f"(d[27]), "+f"(d[28]), "+f"(d[29]), "+f"(d[30]), "+f"(d[31]), "+f"(d[32]), "+f"(d[33]), "+f"(d[34]), "+f"(d[35]),
      "+f"(d[36]), "+f"(d[37]), "+f"(d[38]), "+f"(d[39]), "+f"(d[40]), "+f"(d[41]), "+f"(d[42]), "+f"(d[43]), "+f"(d[44]), "+f"(d[45]), "+f"(d[46]), "+f"(d[47]),
      "+f"(d[48]), "+f"(d[49]), "+f"(d[50]), "+f"(d[51]), "+f"(d[52]), "+f"(d[53]), "+f"(d[54]), "+f"(d[55]), "+f"(d[56]), "+f"(d[57]), "+f"(d[58]), "+f"(d[59]),
      "+f"(d[60]), "+f"(d[61]), "+f"(d[62]), "+f"(d[63]), "+f"(d[64]), "+f"(d[65]), "+f"(d[66]), "+f"(d[67]), "+f"(d[68]), "+f"(d[69]), "+f"(d[70]), "+f"(d[71])
    : "r"(a[0]), "r"(a[1]), "r"(a[2]), "r"(a[3]), "l"(b));
  else asm volatile("wgmma.mma_async.sync.aligned.m64n144k16.f32.bf16.bf16 {%0,%1,%2,%3,%4,%5,%6,%7,%8,%9,%10,%11,%12,%13,%14,%15,%16,%17,%18,%19,%20,%21,%22,%23,%24,%25,%26,%27,%28,%29,%30,%31,%32,%33,%34,%35,%36,%37,%38,%39,%40,%41,%42,%43,%44,%45,%46,%47,%48,%49,%50,%51,%52,%53,%54,%55,%56,%57,%58,%59,%60,%61,%62,%63,%64,%65,%66,%67,%68,%69,%70,%71},{%72,%73,%74,%75},%76,0,1,1,1;"
    : "=f"(d[0]), "=f"(d[1]), "=f"(d[2]), "=f"(d[3]), "=f"(d[4]), "=f"(d[5]), "=f"(d[6]), "=f"(d[7]), "=f"(d[8]), "=f"(d[9]), "=f"(d[10]), "=f"(d[11]),
      "=f"(d[12]), "=f"(d[13]), "=f"(d[14]), "=f"(d[15]), "=f"(d[16]), "=f"(d[17]), "=f"(d[18]), "=f"(d[19]), "=f"(d[20]), "=f"(d[21]), "=f"(d[22]), "=f"(d[23]),
      "=f"(d[24]), "=f"(d[25]), "=f"(d[26]), "=f"(d[27]), "=f"(d[28]), "=f"(d[29]), "=f"(d[30]), "=f"(d[31]), "=f"(d[32]), "=f"(d[33]), "=f"(d[34]), "=f"(d[35]),
      "=f"(d[36]), "=f"(d[37]), "=f"(d[38]), "=f"(d[39]), "=f"(d[40]), "=f"(d[41]), "=f"(d[42]), "=f"(d[43]), "=f"(d[44]), "=f"(d[45]), "=f"(d[46]), "=f"(d[47]),
      "=f"(d[48]), "=f"(d[49]), "=f"(d[50]), "=f"(d[51]), "=f"(d[52]), "=f"(d[53]), "=f"(d[54]), "=f"(d[55]), "=f"(d[56]), "=f"(d[57]), "=f"(d[58]), "=f"(d[59]),
      "=f"(d[60]), "=f"(d[61]), "=f"(d[62]), "=f"(d[63]), "=f"(d[64]), "=f"(d[65]), "=f"(d[66]), "=f"(d[67]), "=f"(d[68]), "=f"(d[69]), "=f"(d[70]), "=f"(d[71])
    : "r"(a[0]), "r"(a[1]), "r"(a[2]), "r"(a[3]), "l"(b));
}

template<int ACC> __device__ __forceinline__ void rs168t(float* d, const uint32_t* a, uint64_t b) {
  if (ACC) asm volatile("wgmma.mma_async.sync.aligned.m64n168k16.f32.bf16.bf16 {%0,%1,%2,%3,%4,%5,%6,%7,%8,%9,%10,%11,%12,%13,%14,%15,%16,%17,%18,%19,%20,%21,%22,%23,%24,%25,%26,%27,%28,%29,%30,%31,%32,%33,%34,%35,%36,%37,%38,%39,%40,%41,%42,%43,%44,%45,%46,%47,%48,%49,%50,%51,%52,%53,%54,%55,%56,%57,%58,%59,%60,%61,%62,%63,%64,%65,%66,%67,%68,%69,%70,%71,%72,%73,%74,%75,%76,%77,%78,%79,%80,%81,%82,%83},{%84,%85,%86,%87},%88,1,1,1,1;"
    : "+f"(d[0]), "+f"(d[1]), "+f"(d[2]), "+f"(d[3]), "+f"(d[4]), "+f"(d[5]), "+f"(d[6]), "+f"(d[7]), "+f"(d[8]), "+f"(d[9]), "+f"(d[10]), "+f"(d[11]),
      "+f"(d[12]), "+f"(d[13]), "+f"(d[14]), "+f"(d[15]), "+f"(d[16]), "+f"(d[17]), "+f"(d[18]), "+f"(d[19]), "+f"(d[20]), "+f"(d[21]), "+f"(d[22]), "+f"(d[23]),
      "+f"(d[24]), "+f"(d[25]), "+f"(d[26]), "+f"(d[27]), "+f"(d[28]), "+f"(d[29]), "+f"(d[30]), "+f"(d[31]), "+f"(d[32]), "+f"(d[33]), "+f"(d[34]), "+f"(d[35]),
      "+f"(d[36]), "+f"(d[37]), "+f"(d[38]), "+f"(d[39]), "+f"(d[40]), "+f"(d[41]), "+f"(d[42]), "+f"(d[43]), "+f"(d[44]), "+f"(d[45]), "+f"(d[46]), "+f"(d[47]),
      "+f"(d[48]), "+f"(d[49]), "+f"(d[50]), "+f"(d[51]), "+f"(d[52]), "+f"(d[53]), "+f"(d[54]), "+f"(d[55]), "+f"(d[56]), "+f"(d[57]), "+f"(d[58]), "+f"(d[59]),
      "+f"(d[60]), "+f"(d[61]), "+f"(d[62]), "+f"(d[63]), "+f"(d[64]), "+f"(d[65]), "+f"(d[66]), "+f"(d[67]), "+f"(d[68]), "+f"(d[69]), "+f"(d[70]), "+f"(d[71]),
      "+f"(d[72]), "+f"(d[73]), "+f"(d[74]), "+f"(d[75]), "+f"(d[76]), "+f"(d[77]), "+f"(d[78]), "+f"(d[79]), "+f"(d[80]), "+f"(d[81]), "+f"(d[82]), "+f"(d[83])
    : "r"(a[0]), "r"(a[1]), "r"(a[2]), "r"(a[3]), "l"(b));
  else asm volatile("wgmma.mma_async.sync.aligned.m64n168k16.f32.bf16.bf16 {%0,%1,%2,%3,%4,%5,%6,%7,%8,%9,%10,%11,%12,%13,%14,%15,%16,%17,%18,%19,%20,%21,%22,%23,%24,%25,%26,%27,%28,%29,%30,%31,%32,%33,%34,%35,%36,%37,%38,%39,%40,%41,%42,%43,%44,%45,%46,%47,%48,%49,%50,%51,%52,%53,%54,%55,%56,%57,%58,%59,%60,%61,%62,%63,%64,%65,%66,%67,%68,%69,%70,%71,%72,%73,%74,%75,%76,%77,%78,%79,%80,%81,%82,%83},{%84,%85,%86,%87},%88,0,1,1,1;"
    : "=f"(d[0]), "=f"(d[1]), "=f"(d[2]), "=f"(d[3]), "=f"(d[4]), "=f"(d[5]), "=f"(d[6]), "=f"(d[7]), "=f"(d[8]), "=f"(d[9]), "=f"(d[10]), "=f"(d[11]),
      "=f"(d[12]), "=f"(d[13]), "=f"(d[14]), "=f"(d[15]), "=f"(d[16]), "=f"(d[17]), "=f"(d[18]), "=f"(d[19]), "=f"(d[20]), "=f"(d[21]), "=f"(d[22]), "=f"(d[23]),
      "=f"(d[24]), "=f"(d[25]), "=f"(d[26]), "=f"(d[27]), "=f"(d[28]), "=f"(d[29]), "=f"(d[30]), "=f"(d[31]), "=f"(d[32]), "=f"(d[33]), "=f"(d[34]), "=f"(d[35]),
      "=f"(d[36]), "=f"(d[37]), "=f"(d[38]), "=f"(d[39]), "=f"(d[40]), "=f"(d[41]), "=f"(d[42]), "=f"(d[43]), "=f"(d[44]), "=f"(d[45]), "=f"(d[46]), "=f"(d[47]),
      "=f"(d[48]), "=f"(d[49]), "=f"(d[50]), "=f"(d[51]), "=f"(d[52]), "=f"(d[53]), "=f"(d[54]), "=f"(d[55]), "=f"(d[56]), "=f"(d[57]), "=f"(d[58]), "=f"(d[59]),
      "=f"(d[60]), "=f"(d[61]), "=f"(d[62]), "=f"(d[63]), "=f"(d[64]), "=f"(d[65]), "=f"(d[66]), "=f"(d[67]), "=f"(d[68]), "=f"(d[69]), "=f"(d[70]), "=f"(d[71]),
      "=f"(d[72]), "=f"(d[73]), "=f"(d[74]), "=f"(d[75]), "=f"(d[76]), "=f"(d[77]), "=f"(d[78]), "=f"(d[79]), "=f"(d[80]), "=f"(d[81]), "=f"(d[82]), "=f"(d[83])
    : "r"(a[0]), "r"(a[1]), "r"(a[2]), "r"(a[3]), "l"(b));
}

template<int ACC> __device__ __forceinline__ void rs192t(float* d, const uint32_t* a, uint64_t b) {
  if (ACC) asm volatile("wgmma.mma_async.sync.aligned.m64n192k16.f32.bf16.bf16 {%0,%1,%2,%3,%4,%5,%6,%7,%8,%9,%10,%11,%12,%13,%14,%15,%16,%17,%18,%19,%20,%21,%22,%23,%24,%25,%26,%27,%28,%29,%30,%31,%32,%33,%34,%35,%36,%37,%38,%39,%40,%41,%42,%43,%44,%45,%46,%47,%48,%49,%50,%51,%52,%53,%54,%55,%56,%57,%58,%59,%60,%61,%62,%63,%64,%65,%66,%67,%68,%69,%70,%71,%72,%73,%74,%75,%76,%77,%78,%79,%80,%81,%82,%83,%84,%85,%86,%87,%88,%89,%90,%91,%92,%93,%94,%95},{%96,%97,%98,%99},%100,1,1,1,1;"
    : "+f"(d[0]), "+f"(d[1]), "+f"(d[2]), "+f"(d[3]), "+f"(d[4]), "+f"(d[5]), "+f"(d[6]), "+f"(d[7]), "+f"(d[8]), "+f"(d[9]), "+f"(d[10]), "+f"(d[11]),
      "+f"(d[12]), "+f"(d[13]), "+f"(d[14]), "+f"(d[15]), "+f"(d[16]), "+f"(d[17]), "+f"(d[18]), "+f"(d[19]), "+f"(d[20]), "+f"(d[21]), "+f"(d[22]), "+f"(d[23]),
      "+f"(d[24]), "+f"(d[25]), "+f"(d[26]), "+f"(d[27]), "+f"(d[28]), "+f"(d[29]), "+f"(d[30]), "+f"(d[31]), "+f"(d[32]), "+f"(d[33]), "+f"(d[34]), "+f"(d[35]),
      "+f"(d[36]), "+f"(d[37]), "+f"(d[38]), "+f"(d[39]), "+f"(d[40]), "+f"(d[41]), "+f"(d[42]), "+f"(d[43]), "+f"(d[44]), "+f"(d[45]), "+f"(d[46]), "+f"(d[47]),
      "+f"(d[48]), "+f"(d[49]), "+f"(d[50]), "+f"(d[51]), "+f"(d[52]), "+f"(d[53]), "+f"(d[54]), "+f"(d[55]), "+f"(d[56]), "+f"(d[57]), "+f"(d[58]), "+f"(d[59]),
      "+f"(d[60]), "+f"(d[61]), "+f"(d[62]), "+f"(d[63]), "+f"(d[64]), "+f"(d[65]), "+f"(d[66]), "+f"(d[67]), "+f"(d[68]), "+f"(d[69]), "+f"(d[70]), "+f"(d[71]),
      "+f"(d[72]), "+f"(d[73]), "+f"(d[74]), "+f"(d[75]), "+f"(d[76]), "+f"(d[77]), "+f"(d[78]), "+f"(d[79]), "+f"(d[80]), "+f"(d[81]), "+f"(d[82]), "+f"(d[83]),
      "+f"(d[84]), "+f"(d[85]), "+f"(d[86]), "+f"(d[87]), "+f"(d[88]), "+f"(d[89]), "+f"(d[90]), "+f"(d[91]), "+f"(d[92]), "+f"(d[93]), "+f"(d[94]), "+f"(d[95])
    : "r"(a[0]), "r"(a[1]), "r"(a[2]), "r"(a[3]), "l"(b));
  else asm volatile("wgmma.mma_async.sync.aligned.m64n192k16.f32.bf16.bf16 {%0,%1,%2,%3,%4,%5,%6,%7,%8,%9,%10,%11,%12,%13,%14,%15,%16,%17,%18,%19,%20,%21,%22,%23,%24,%25,%26,%27,%28,%29,%30,%31,%32,%33,%34,%35,%36,%37,%38,%39,%40,%41,%42,%43,%44,%45,%46,%47,%48,%49,%50,%51,%52,%53,%54,%55,%56,%57,%58,%59,%60,%61,%62,%63,%64,%65,%66,%67,%68,%69,%70,%71,%72,%73,%74,%75,%76,%77,%78,%79,%80,%81,%82,%83,%84,%85,%86,%87,%88,%89,%90,%91,%92,%93,%94,%95},{%96,%97,%98,%99},%100,0,1,1,1;"
    : "=f"(d[0]), "=f"(d[1]), "=f"(d[2]), "=f"(d[3]), "=f"(d[4]), "=f"(d[5]), "=f"(d[6]), "=f"(d[7]), "=f"(d[8]), "=f"(d[9]), "=f"(d[10]), "=f"(d[11]),
      "=f"(d[12]), "=f"(d[13]), "=f"(d[14]), "=f"(d[15]), "=f"(d[16]), "=f"(d[17]), "=f"(d[18]), "=f"(d[19]), "=f"(d[20]), "=f"(d[21]), "=f"(d[22]), "=f"(d[23]),
      "=f"(d[24]), "=f"(d[25]), "=f"(d[26]), "=f"(d[27]), "=f"(d[28]), "=f"(d[29]), "=f"(d[30]), "=f"(d[31]), "=f"(d[32]), "=f"(d[33]), "=f"(d[34]), "=f"(d[35]),
      "=f"(d[36]), "=f"(d[37]), "=f"(d[38]), "=f"(d[39]), "=f"(d[40]), "=f"(d[41]), "=f"(d[42]), "=f"(d[43]), "=f"(d[44]), "=f"(d[45]), "=f"(d[46]), "=f"(d[47]),
      "=f"(d[48]), "=f"(d[49]), "=f"(d[50]), "=f"(d[51]), "=f"(d[52]), "=f"(d[53]), "=f"(d[54]), "=f"(d[55]), "=f"(d[56]), "=f"(d[57]), "=f"(d[58]), "=f"(d[59]),
      "=f"(d[60]), "=f"(d[61]), "=f"(d[62]), "=f"(d[63]), "=f"(d[64]), "=f"(d[65]), "=f"(d[66]), "=f"(d[67]), "=f"(d[68]), "=f"(d[69]), "=f"(d[70]), "=f"(d[71]),
      "=f"(d[72]), "=f"(d[73]), "=f"(d[74]), "=f"(d[75]), "=f"(d[76]), "=f"(d[77]), "=f"(d[78]), "=f"(d[79]), "=f"(d[80]), "=f"(d[81]), "=f"(d[82]), "=f"(d[83]),
      "=f"(d[84]), "=f"(d[85]), "=f"(d[86]), "=f"(d[87]), "=f"(d[88]), "=f"(d[89]), "=f"(d[90]), "=f"(d[91]), "=f"(d[92]), "=f"(d[93]), "=f"(d[94]), "=f"(d[95])
    : "r"(a[0]), "r"(a[1]), "r"(a[2]), "r"(a[3]), "l"(b));
}

template<int NP> __device__ __forceinline__ float4 row_stats(const uint32_t (*y)[4]) {
  float m[2], q[2];
#pragma unroll
  for (int r = 0; r < 2; r++) {
    m[r] = 0.f;
#pragma unroll
    for (int i = 0; i < NP; i++) m[r] += (blo(y[i][r]) + bhi(y[i][r])) + (blo(y[i][r + 2]) + bhi(y[i][r + 2]));
  }
#pragma unroll
  for (int o = 1; o < 4; o *= 2) { m[0] += __shfl_xor_sync(~0u, m[0], o); m[1] += __shfl_xor_sync(~0u, m[1], o); }
#pragma unroll
  for (int r = 0; r < 2; r++) {
    m[r] *= (1.f / (16 * NP)); q[r] = 0.f;
#pragma unroll
    for (int i = 0; i < 2 * NP; i++) { const uint32_t v = y[i >> 1][r + (i & 1) * 2]; const float a = blo(v) - m[r], b = bhi(v) - m[r]; q[r] += a * a + b * b; }
  }
#pragma unroll
  for (int o = 1; o < 4; o *= 2) { q[0] += __shfl_xor_sync(~0u, q[0], o); q[1] += __shfl_xor_sync(~0u, q[1], o); }
  return make_float4(m[0], q[0], m[1], q[1]);
}

constexpr uint32_t PL = 9472, PG = 9216;
constexpr uint32_t H_MEM = 0, H_QB = 94720, H_KB = 104960, H_VB = 115200, H_ZERO = H_VB + 10240, H_OS = 127488, H_ST = 135680, H_OM = 143872,
                   H_WO = 152320, H_DUMP = 203520, H_BAR = 203648, H_LN = 203904, H_WL = 204672, H_TRC = 147968;
constexpr uint32_t H_SMEM = H_WL + 6 * 4096;
constexpr int KR = KRV;
constexpr uint32_t WLS = (37 - KR) * 256;
constexpr int NM = 16 + 8 * EX, NB = 64 - 8 * EX;
constexpr uint32_t B_MEM = H_BAR, B_XT = H_BAR + 32, B_XB = H_BAR + 40, B_MD = H_BAR + 48, B_QK = H_BAR + 64, B_V = H_BAR + 72,
                   B_OM = H_BAR + 80, B_W2 = H_BAR + 88, B_W3 = H_BAR + 96, B_OS = H_BAR + 104, B_ST = H_BAR + 112, B_XA = H_BAR + 120, B_WS = H_BAR + 56, B_XC = H_BAR + 128, B_TD = H_BAR + 136;

__device__ __forceinline__ void cluster_sync() { asm volatile("barrier.cluster.arrive.release.aligned; barrier.cluster.wait.acquire.aligned;" ::: "memory"); }

template<int N, int KK> __device__ __forceinline__ void proj_step(float* acc, const uint32_t* w, uint64_t d, uint64_t wl) {
  constexpr int A = KK != 36;
  if constexpr (KK < KR) {
    if (N == 24) rs24<A>(acc, &w[KK * 4], d + KK * 16); if (N == 32) rs32<A>(acc, &w[KK * 4], d + KK * 16);
    if (N == 48) rs48<A>(acc, &w[KK * 4], d + KK * 16); if (N == 56) rs56<A>(acc, &w[KK * 4], d + KK * 16);
  } else {
    if (N == 24) ss24tn<A>(acc, wl + (KK - KR) * 16, d + KK * 16); if (N == 32) ss32tn<A>(acc, wl + (KK - KR) * 16, d + KK * 16);
    if (N == 48) ss48tn<A>(acc, wl + (KK - KR) * 16, d + KK * 16); if (N == 56) ss56tn<A>(acc, wl + (KK - KR) * 16, d + KK * 16);
  }
}
template<int N, int K0, int K1> __device__ __forceinline__ void proj_loop(float* acc, const uint32_t* w, uint64_t d, uint64_t wl) {
  if constexpr (K0 < K1) { proj_step<N, K0>(acc, w, d, wl); proj_loop<N, K0 + 1, K1>(acc, w, d, wl); }
}
template<int N, int K0, int K1> __device__ __forceinline__ void proj_steps(float* acc, const uint32_t* w, uint64_t d, uint64_t wl) {
  if constexpr (K0 < K1) { wg_fence(); proj_loop<N, K0, K1>(acc, w, d, wl); wg_commit(); }
}

template<int J> __device__ __forceinline__ void h_proj(const uint32_t sb, const int wg, const int w, const int lane) {
  uint32_t wr[KR * 4];
  {
    const uint32_t a = sb + (wg * 8 + w * 2 + ((lane >> 3) & 1)) * 16 + ((lane >> 4) * 8 + (lane & 7)) * 272;
#pragma unroll
    for (int kk = 0; kk < KR; kk++) ldsm4t(&wr[kk * 4], a + kk * 16 * 272);
  }
  float cq[3][4] = {};
#pragma unroll
  for (int kk = 0; kk < 36; kk++) {
    uint32_t t[4];
    if (kk >= KR) ldsm4t(t, sb + H_WL + (wg * 8 + w * 2 + ((lane >> 3) & 1)) * WLS + ((kk - KR) * 16 + (lane >> 4) * 8 + (lane & 7)) * 16);
    const uint32_t* a = kk < KR ? &wr[kk * 4] : t;
    HMMA(cq[kk % 3], a[0], a[1], a[2], a[3], 0x3F803F80u, 0x3F803F80u);
  }
  const float cs0 = cq[0][0] + cq[1][0] + cq[2][0], cs1 = cq[0][2] + cq[1][2] + cq[2][2];
  {
    const uint32_t a = sb + H_WL + (wg * 8 + w * 2) * WLS + (36 - KR) * 256;
    sts4(a + (lane >> 4) * WLS + (lane & 15) * 16, 0, 0, 0, 0);
    __syncwarp();
    const uint32_t hi = pk(cs0, cs1), lo = pk(cs0 - blo(hi), cs1 - bhi(hi)), v = (lane & 3) == 1 ? lo : hi;
    if ((lane & 3) < 3) {
      asm volatile("st.shared.b16 [%0], %1;" :: "r"(a + (lane & 3) * 16 + (lane >> 2) * 2), "h"((uint16_t)v) : "memory");
      asm volatile("st.shared.b16 [%0], %1;" :: "r"(a + WLS + (lane & 3) * 16 + (lane >> 2) * 2), "h"((uint16_t)(v >> 16)) : "memory");
    }
    fence_async();
  }
  asm volatile("bar.sync 1, 512;" ::: "memory");
  cluster_sync();
  constexpr uint32_t BUF = J == 0 ? H_QB : J == 1 ? H_KB : H_VB, BAR = J == 2 ? B_V : B_QK;
  const uint32_t so = sb & 0x1FFFFFF;
  const uint32_t dst = so + BUF + 8192 + (wg * 8 + w * 2) * 128 + lane * 4;
  const uint64_t wl = mkdesc(sb + H_WL + wg * 8 * WLS, 128, WLS);
  const uint64_t md = mkdesc(sb + H_MEM, 128, PL);
  static_assert(EX == 2, "token blocks are normalised in pairs");
  uint32_t pt[4];
  auto scale = [&](uint32_t* p, const float* a, const float4 r) {
    p[0] = pk(a[0] * r.x, a[1] * r.y); p[1] = pk(a[2] * r.x, a[3] * r.y); p[2] = pk(a[4] * r.z, a[5] * r.w); p[3] = pk(a[6] * r.z, a[7] * r.w);
  };
  const uint32_t lna = sb + H_LN + (lane & 3) * 32;
  auto put = [&](const uint32_t* p) {
    const uint32_t a = sb + (wg * 8 + w * 2) * 128 + (lane >> 3) * 2048 + (lane & 7) * 16;
#pragma unroll
    for (int L = 0; L < 2; L++) {
      const uint32_t b = a + (J == 2 ? (L ? H_KB : H_QB) : L == J ? BUF : H_ST);
      stsm4(b, p[8 * L], p[8 * L + 2], p[8 * L + 4], p[8 * L + 6]);
      stsm4(b + 128, p[8 * L + 1], p[8 * L + 3], p[8 * L + 5], p[8 * L + 7]);
    }
    return drain(sb + H_ZERO);
  };
  uint32_t dr;
  {
    float acc[16];
    mbar_wait(sb + B_XB, 0);
    proj_steps<32, 36, 37>(acc, wr, md + 6 * (PL / 16), wl);
    proj_steps<32, 0, 36>(acc, wr, md + 6 * (PL / 16), wl);
    wg_wait<0>(); pin<16>(acc);
    if (lane == 0) mbar_arrive(sb + B_TD);
    uint32_t p[16];
#pragma unroll
    for (int i = 0; i < 2; i++) scale(&p[4 * i], &acc[8 * i], lds_f4(lna + i * 16));
#pragma unroll
    for (int i = 0; i < 8; i++) p[8 + i] = p[i];
    dr = put(p);
    mbar_wait(sb + B_XT, 0);
  }
  for (int s = 0;; s++) {
    float accM[NM / 2], accB[NB / 2];
    if (STP == 0) arrive_after(sb + B_ST, dr, lane);
    proj_steps<NM, 36, 37>(accM, wr, md, wl);
    if (STP == 1) arrive_after(sb + B_ST, dr, lane);
    mbar_wait(sb + B_MEM, s & 1);
    if (wg == 0) { TR(0); }
    proj_steps<NM, 0, 9>(accM, wr, md, wl);
    if (STP == 2) arrive_after(sb + B_ST, dr, lane);
    mbar_wait(sb + B_MEM + 8, s & 1);
    proj_steps<NM, 9, 18>(accM, wr, md, wl);
    mbar_wait(sb + B_MEM + 16, s & 1);
    proj_steps<NM, 18, 27>(accM, wr, md, wl);
    mbar_wait(sb + B_MEM + 24, s & 1);
    if (wg == 0) { TR(6); }
    proj_steps<NM, 27, 36>(accM, wr, md, wl);
    if (lane == 0) mbar_arrive(sb + B_XC);
    const uint32_t lnf = lna + ((s + 1) & 1) * 128;
    const float4 rt = lds_f4(lnf);
    wg_wait<0>(); pin<NM / 2>(accM);
#pragma unroll
    for (int L = 0; L < 2; L++) if (L != J) {
      st_async1(dst + (L << 25), pk(accM[4 * L], accM[4 * L + 1]), so + BAR + (L << 25));
      st_async1(dst + (L << 25) + 128, pk(accM[4 * L + 2], accM[4 * L + 3]), so + BAR + (L << 25));
    }
    if (J < 2) {
      sts1(dst + (J << 25), pk(accM[4 * J], accM[4 * J + 1])); sts1(dst + (J << 25) + 128, pk(accM[4 * J + 2], accM[4 * J + 3]));
      publish(sb + B_QK, sb + H_ZERO, lane);
    }
    TR(1 + wg * 4);
    if (s == NSTEP - 1) break;
    if (lane == 0) mbar_arrive(sb + B_MD);
    const uint64_t bd = md + (2 + EX) * (PL / 16);
    constexpr int NA = J < 2 ? N1 + NS + N2 : NV;
    scale(pt, &accM[8], rt);
    mbar_wait(sb + B_XA, s & 1);
    wg_fence(); proj_loop<NB, 36, 37>(accB, wr, bd, wl); proj_loop<NB, 0, N1>(accB, wr, bd, wl); wg_commit();
    if (J < 2 && NS > 0) mbar_wait(sb + B_WS, s & 1);
    proj_steps<NB, N1, N1 + NS>(accB, wr, bd, wl);
    mbar_wait(sb + B_XB, (s + 1) & 1);
    if (J < 2 && N2 > 0) mbar_wait(sb + B_W2, s & 1);
    proj_steps<NB, N1 + NS, NA>(accB, wr, bd, wl);
    mbar_wait(sb + B_W3, s & 1);
    if (wg == 0) { TR(2); }
    proj_steps<NB, NA, 36>(accB, wr, bd, wl);
    mbar_wait(sb + B_XT, (s + 1) & 1);
    float4 r0, r1, r2;
    if (RPF > 0) r0 = lds_f4(lnf + 16);
    if (RPF > 1) r1 = lds_f4(lnf + 256);
    if (RPF > 2) r2 = lds_f4(lnf + 256 + 16);
    wg_wait<0>(); pin<NB / 2>(accB);
    if (wg == 0) { TR(3); }
    if (lane == 0) mbar_arrive(sb + B_TD);
    uint32_t p[16];
    if (RPF < 1) r0 = lds_f4(lnf + 16);
    if (RPF < 2) r1 = lds_f4(lnf + 256);
    if (RPF < 3) r2 = lds_f4(lnf + 256 + 16);
#pragma unroll
    for (int i = 0; i < 4; i++) p[i] = pt[i];
    scale(&p[4], &accB[0], r0); scale(&p[8], &accB[8], r1); scale(&p[12], &accB[16], r2);
    dr = put(p);
  }
}

template<int J> __device__ __forceinline__ void h_chain(uint8_t* smraw, const uint32_t sb, const int w, int lane, const uint32_t epoch, const bf16* __restrict__ mem0) {
  asm volatile("bar.sync 1, 512;" ::: "memory");
#pragma unroll 1
  for (int i = w * 144 + lane; i < w * 144 + 144; i += 32) {
    const uint4 v = *(const uint4*)(mem0 + (i & 7) * 576 + (i >> 3) * 8);
    *(uint4*)(smraw + H_MEM + i * 16) = v; *(uint4*)(smraw + H_MEM + PL + i * 16) = v;
  }
  *(uint4*)(smraw + H_ZERO + (w * 32 + lane) * 16) = make_uint4(0, 0, 0, 0);
  for (int i = w * 32 + lane; i < 160; i += 128) *(uint4*)(smraw + H_MEM + (i >> 4) * PL + PG + (i & 15) * 16) = make_uint4(0, 0, 0, 0);
  asm volatile("bar.sync 2, 128;" ::: "memory");
  fence_async();
  __syncwarp();
  if (ARM ? lane < 4 : lane == w) mbar_arrive(sb + B_MEM + lane * 8);
  cluster_sync();
  const uint32_t so = sb & 0x1FFFFFF;
  uint32_t pd = PD;
  for (int s = 0;; s++) {
    const uint32_t par = s & 1;
    lane = lane_id();
    const float cs = 0.08838834764831845f * 1.4426950408889634f;
    const uint32_t wb = sb + H_WO + w * 48 + lane * 400;
    uint32_t bq[4][12];
    if (J < 2) {
      float sc[20];
      uint32_t pa[12];
      asm volatile("ld.shared.v2.b32 {%0,%1}, [%2];" : "=r"(pa[10]), "=r"(pa[11]) : "r"(sb + H_ZERO));
      const uint64_t qd = mkdesc(sb + H_QB, 128, 2048), kd = mkdesc(sb + H_KB, 128, 2048), vd = mkdesc(sb + H_VB, 2048, 128);
      mbar_wait(sb + B_QK, par);
      TR(8);
      wg_fence();
#pragma unroll
      for (int kk = 0; kk < 8; kk++) { if (kk == 0) ss40tt<0>(sc, qd, kd); else ss40tt<1>(sc, qd + kk * 16, kd + kk * 16); }
      wg_commit();
      if (VW == 0) mbar_wait(sb + B_V, par);
      wg_wait<0>(); pin<20>(sc);
      if (NS > 0 && w == 3 && lane == 0) mbar_arrive(sb + B_WS);
      TR(7);
      float s0 = 0.f, s1 = 0.f;
      if (w < 2) {
        const int r0 = (lane >> 2) * 2 + w - 4 * (lane & 3);
        float m0 = fmaxf(sc[16], sc[17]), m1 = fmaxf(sc[18], sc[19]);
#pragma unroll
        for (int i = 0; i < 4; i += 2) {
          const int c = i >> 1;
          const bool k0 = c > r0, k1 = c + 2 > r0;
          if (k0) { sc[4 * i] = -INFINITY; sc[4 * i + 6] = -INFINITY; }
          if (k1) { sc[4 * i + 1] = -INFINITY; sc[4 * i + 7] = -INFINITY; }
          m0 = fmaxf(m0, fmaxf(sc[4 * i], sc[4 * i + 1]));
          m1 = fmaxf(m1, fmaxf(fmaxf(sc[4 * i + 2], sc[4 * i + 3]), fmaxf(sc[4 * i + 6], sc[4 * i + 7])));
        }
        m1 = fmaxf(m1, __shfl_xor_sync(~0u, m1, 1)); m0 = fmaxf(m0, __shfl_xor_sync(~0u, m0, 1));
        m1 = fmaxf(m1, __shfl_xor_sync(~0u, m1, 2)); m0 = fmaxf(m0, __shfl_xor_sync(~0u, m0, 2));
        m0 *= cs; m1 *= cs;
#pragma unroll
        for (int i = 0; i < 5; i++) {
          if (i & 1) pa[2 * i] = pa[10];
          else {
            const float a = ex2(fmaf(sc[4 * i], cs, -m0)), b = ex2(fmaf(sc[4 * i + 1], cs, -m0));
            s0 += a + b; pa[2 * i] = pk(a, b);
          }
          const float a = ex2(fmaf(sc[4 * i + 2], cs, -m1)), b = ex2(fmaf(sc[4 * i + 3], cs, -m1));
          s1 += a + b; pa[2 * i + 1] = pk(a, b);
        }
      } else {
        float m0 = fmaxf(fmaxf(fmaxf(sc[0], sc[1]), fmaxf(sc[4], sc[5])), fmaxf(fmaxf(fmaxf(sc[8], sc[9]), fmaxf(sc[12], sc[13])), fmaxf(sc[16], sc[17])));
        m0 = fmaxf(m0, __shfl_xor_sync(~0u, m0, 1));
        m0 = fmaxf(m0, __shfl_xor_sync(~0u, m0, 2));
        m0 *= cs;
#pragma unroll
        for (int i = 0; i < 5; i++) {
          const float a = ex2(fmaf(sc[4 * i], cs, -m0)), b = ex2(fmaf(sc[4 * i + 1], cs, -m0));
          s0 += a + b; pa[2 * i] = pk(a, b); pa[2 * i + 1] = pa[10];
        }
        if (VW == 1) mbar_wait(sb + B_V, par);
      }
      TR(4);
      float o[2][32];
      wg_fence();
      rs64<0>(o[0], pa, vd); rs64<1>(o[0], pa + 4, vd + 256); rs64<1>(o[0], pa + 8, vd + 512); wg_commit();
      rs64<0>(o[1], pa, vd + 64); rs64<1>(o[1], pa + 4, vd + 64 + 256); rs64<1>(o[1], pa + 8, vd + 64 + 512); wg_commit();
      s0 += __shfl_xor_sync(~0u, s0, 1); s1 += __shfl_xor_sync(~0u, s1, 1);
      s0 += __shfl_xor_sync(~0u, s0, 2); s1 += __shfl_xor_sync(~0u, s1, 2);
      s0 = rcp(s0); s1 = rcp(s1);
      if (w == 2 && s < NSTEP - 1) {
        const uint32_t omo = so + H_OM + J * 2048 + (lane & 3) * 128 + (((lane >> 2) ^ ((lane & 3) * 2)) * 16);
        constexpr uint32_t R1 = (uint32_t)(1 - J) << 25, R2 = 2u << 25, RL = (uint32_t)J << 25;
        uint32_t x[16];
#pragma unroll
        for (int hf = 0; hf < 2; hf++) {
          if (hf == 0) wg_wait<1>(); else wg_wait<0>();
          pin<32>(o[hf]);
#pragma unroll
          for (int jg = 2 * hf; jg < 2 * hf + 2; jg++) {
#pragma unroll
            for (int i = 0; i < 4; i++) x[4 * jg + i] = pk(o[hf][(jg & 1) * 16 + 4 * i] * s0, o[hf][(jg & 1) * 16 + 4 * i + 1] * s0);
            st_async4(omo + jg * 512 + R1, x[4 * jg], x[4 * jg + 1], x[4 * jg + 2], x[4 * jg + 3], so + B_OM + R1);
            st_async4(omo + jg * 512 + R2, x[4 * jg], x[4 * jg + 1], x[4 * jg + 2], x[4 * jg + 3], so + B_OM + R2);
          }
        }
#pragma unroll
        for (int jg = 0; jg < 4; jg++) sts4(omo + jg * 512 + RL, x[4 * jg], x[4 * jg + 1], x[4 * jg + 2], x[4 * jg + 3]);
        __syncwarp();
        if (lane == 0) { mbar_arrive(sb + B_OM); if (N2 > 0) mbar_arrive(sb + B_W2); }
        TRW(9, 2);
      } else {
        wg_wait<0>();
        pin<32>(o[0]); pin<32>(o[1]);
        if (w < 2) {
          const uint32_t os = sb + H_OS + w * 4096 + lane * 16;
          const uint32_t otag = ORING == NSEG ? (epoch + 1) & 1 : (((uint32_t)(s - J * LAG) / ORING) + 1) & 1;
#pragma unroll
          for (int kk = 0; kk < 8; kk++) {
            const float* oo = &o[kk >> 2][(kk & 3) * 8];
            sts4(os + kk * 512, pk_tag(oo[0] * s0, oo[1] * s0, otag), pk(oo[2] * s1, oo[3] * s1), pk(oo[4] * s0, oo[5] * s0), pk(oo[6] * s1, oo[7] * s1));
          }
        }
      }
    }
#pragma unroll
    for (int u = 0; u < 4; u++)
#pragma unroll
      for (int tt = 0; tt < 3; tt++) ldsm4t(&bq[u][tt * 4], wb + tt * 16 + u * 12800);
    const bool u0 = s < NSEG - 1, u1 = s >= LAG;
    uint4* const gacc = &g_acc[0][0] + ((s == NSTEP - 2 ? 4 : s & 3) * 48 * AG + (lane >> 3) * (AG / 4) + (lane & 7));
    if (s < NSTEP - 1) {
      uint4* const pacc = gacc + ((w >> 1) * 12 + J * 2 + (w & 1)) * AG;
      const uint32_t oa = sb + H_OM + ((lane >> 3) & 1) * 2048 + (lane >> 4) * 128 + (((lane & 7) ^ ((lane >> 4) * 2)) * 16);
      mbar_wait(sb + B_OM, par);
      TR(10);
      uint32_t A[8][4];
#pragma unroll
      for (int kk = 0; kk < 8; kk++) ldsm4(A[kk], (oa ^ ((kk & 1) * 64)) + kk * 256);
#pragma unroll
      for (int a = 0; a < 2; a++) {
        float d[3][4];
#pragma unroll
        for (int tt = 0; tt < 3; tt++) { d[tt][0] = d[tt][1] = d[tt][2] = d[tt][3] = 0.f; }
#pragma unroll
        for (int jg = 0; jg < 4; jg++) {
          uint32_t* b = bq[jg];
#pragma unroll
          for (int tt = 0; tt < 3; tt++) HMMA(d[tt], A[2 * jg][0], A[2 * jg][1], A[2 * jg][2], A[2 * jg][3], b[tt * 4], b[tt * 4 + 1]);
          if (a == 0 && jg > 0) {
#pragma unroll
            for (int tt = 0; tt < 3; tt++) ldsm4t(&bq[jg - 1][tt * 4], wb + 192 + tt * 16 + (jg - 1) * 12800);
          }
          if (a == 1 && jg == 0) {
#pragma unroll
            for (int tt = 0; tt < 3; tt++) ldsm4t(&bq[3][tt * 4], wb + 192 + tt * 16 + 3 * 12800);
          }
#pragma unroll
          for (int tt = 0; tt < 3; tt++) HMMA(d[tt], A[2 * jg + 1][0], A[2 * jg + 1][1], A[2 * jg + 1][2], A[2 * jg + 1][3], b[tt * 4 + 2], b[tt * 4 + 3]);
        }
        red4(pacc + a * 24 * AG, pk(d[0][0], d[0][1]), pk(d[1][0], d[1][1]), pk(d[2][0], d[2][1]), u0);
        red4(pacc + (a * 24 + 6) * AG, pk(d[0][2], d[0][3]), pk(d[1][2], d[1][3]), pk(d[2][2], d[2][3]), u1);
      }
      if (lane == 0) mbar_arrive(sb + B_W3);
    }
    const uint32_t c0 = clock();
    TR(11);
    if (J < 2 && w < 2) publish(sb + B_OS, sb + H_ZERO, lane);
    if (s == NSTEP - 1) break;
    {
      const uint32_t ch = w ^ 2, lf = blockIdx.x & 1;
      const uint32_t la = (u0 && u1) ? lf : u1, lb = (u0 && u1) ? 1 - lf : u1;
      const uint4* const pa_ = gacc + (ch * 12 + la * 6) * AG;
      const uint4* const pb_ = gacc + (ch * 12 + lb * 6) * AG;
      const uint32_t ma = sb + H_MEM + la * PL + ch * 2304 + lane * 16, mb = sb + H_MEM + lb * PL + ch * 2304 + lane * 16;
      const uint32_t ma5 = lane < 24 ? ma + 1920 : sb + H_DUMP + (lane & 7) * 16, mb5 = lane < 24 ? mb + 1920 : ma5;
      const uint32_t dl = PD + ch * PDS + (ch >> 1) * PDH;
      while ((uint32_t)clock() - c0 < dl) {}
      uint32_t v[12][4];
      uint32_t it = 0;
      while (true) {
#pragma unroll
        for (int i = 0; i < 6; i++) { const int ii = (i + 2 * J) % 6; ld_rlx(v[ii], pa_ + ii * AG); ld_rlx(v[6 + ii], pb_ + ii * AG); }
        uint32_t mn = v[0][3];
#pragma unroll
        for (int i = 1; i < 12; i++) mn &= v[i][3];
#pragma unroll
        for (int i = 0; i < 6; i++) stsm4(i < 5 ? ma + i * 384 : ma5, v[i][0], v[i][1], v[i][2], v[i][3]);
#pragma unroll
        for (int i = 0; i < 6; i++) stsm4(i < 5 ? mb + i * 384 : mb5, v[6 + i][0], v[6 + i][1], v[6 + i][2], v[6 + i][3]);
        const uint32_t d = drain(sb + H_ZERO);
        if (__all_sync(~0u, mn == 0x4200u)) { arrive_after(sb + B_MEM + ch * 8, d, lane); break; }
        if (++it > SPIN_MAX) __trap();
      }
    }
    TRW(14, 2);
  }
}

__device__ __forceinline__ uint32_t x_load(uint32_t sb, uint32_t bar, int L, int s, int p0, int p1, int d0, uint32_t o0, uint32_t o1, uint32_t epoch, uint32_t ln, int lane, float& nm) {
  const int seg = s - L * LAG;
  if ((uint32_t)seg >= (uint32_t)NSEG) return 0;
  if (ln) {
    flag_wait(&g_fXB[L][seg][0], (epoch + 1) * 8);
    asm volatile("fence.proxy.async.global;" ::: "memory");
  }
  if (lane == 0) {
    const uint8_t* src = (const uint8_t*)&g_xb[L][seg][p0 * 576] + o0;
    uint32_t dst = sb + H_MEM + d0 * PL + o0;
#pragma unroll 1
    for (int p = p0; p < p1; p++, src += PG, dst += PL) bulk_g2s(dst, src, o1 - o0, sb + bar);
  }
  if (ln) {
    float m[4], q[4];
#pragma unroll
    for (int c = 0; c < 4; c++) asm volatile("ld.relaxed.gpu.global.v2.f32 {%0,%1}, [%2];" : "=f"(m[c]), "=f"(q[c]) : "l"(&g_stB[L][seg][c][lane]) : "memory");
    nm = -0.25f * ((m[0] + m[1]) + (m[2] + m[3]));
    float v = 0.f;
#pragma unroll
    for (int c = 0; c < 4; c++) v += q[c] + 144.f * (m[c] + nm) * (m[c] + nm);
    sts1(ln + ((lane >> 1) & 3) * 32 + (lane >> 3) * 8 + (lane & 1) * 4, __float_as_uint(rsqrtf(v * (1.f / 576) + 1e-5f)));
  }
  if (o0 == 0 && (lane >> 3) >= p0 && (lane >> 3) < p1) {
    const uint32_t hi = pk(nm, nm);
    asm volatile("st.shared.v2.b32 [%0], {%1,%2};" :: "r"(sb + H_MEM + (d0 - p0 + (lane >> 3)) * PL + PG + (lane & 7) * 16), "r"(hi), "r"(pk(nm - blo(hi), 0.f)) : "memory");
  }
  return (p1 - p0) * (o1 - o0);
}
__device__ __forceinline__ void x_arm(uint32_t sb, uint32_t bar, uint32_t n, int lane) {
  __syncwarp();
  if (drain(sb + H_ZERO) == lane) mbar_expect(sb + bar, n);
}

__device__ __forceinline__ void h_help(const uint32_t sb, const int h, const int j, const int w, const int lane, const uint32_t epoch) {
  asm volatile("bar.sync 1, 512;" ::: "memory");
  cluster_sync();
  if (w == 0) {
    constexpr uint32_t XS = (N1 + NS) * 256;
    float nf, ns;
    x_arm(sb, B_XB, x_load(sb, B_XB, 0, 0, 0, 4, 6, 0, PG, epoch, sb + H_LN, lane, nf), lane);
    x_arm(sb, B_XT, x_load(sb, B_XT, 0, 1, 0, EX, 2, 0, PG, epoch, sb + H_LN + 128, lane, nf), lane);
#pragma unroll 1
    for (int s = 0; s < NSTEP - 1; s++) {
      mbar_wait(sb + B_TD, s & 1);
      uint32_t n = x_load(sb, B_XA, 0, s + 1, EX, 4, 2 + EX, 0, XS, epoch, 0, lane, nf);
      x_arm(sb, B_XA, n + x_load(sb, B_XA, 1, s + 1, 0, 4, 6, 0, XS, epoch, sb + H_LN + 256 + ((s + 1) & 1) * 128, lane, ns), lane);
      mbar_wait(sb + B_XC, s & 1);
      n = x_load(sb, B_XB, 0, s + 1, EX, 4, 2 + EX, XS, PG, epoch, 0, lane, nf);
      n += x_load(sb, B_XB, 1, s + 1, 0, 4, 6, XS, PG, epoch, 0, lane, ns);
      if (lane == 0) mbar_expect(sb + B_XB, n);
      mbar_wait(sb + B_MD, s & 1);
      x_arm(sb, B_XT, x_load(sb, B_XT, 0, s + 2, 0, EX, 2, 0, PG, epoch, sb + H_LN + (s & 1) * 128, lane, nf), lane);
    }
  } else if (w == 1) {
    if (lane == 0 && j < 2) {
#pragma unroll 1
      for (int s = 0; s < NSTEP; s++) {
        const int seg = s - j * LAG;
        mbar_wait(sb + B_OS, s & 1);
        mbar_expect(sb + B_QK, 10240);
        if ((uint32_t)seg < (uint32_t)NSEG) {
          if (OD > 0 && s < NSTEP - 1) __nanosleep(OD);
          uint4* po = &g_O[j][seg % ORING][0][8 * h][0];
          asm volatile("cp.async.bulk.global.shared::cta.bulk_group [%0], [%1], 4096;" :: "l"(po), "r"(sb + H_OS) : "memory");
          asm volatile("cp.async.bulk.global.shared::cta.bulk_group [%0], [%1], 4096;" :: "l"(po + 8192), "r"(sb + H_OS + 4096) : "memory");
          asm volatile("cp.async.bulk.commit_group; cp.async.bulk.wait_group.read 0;" ::: "memory");
          mbar_expect(sb + B_V, 10240);
          if (OW) asm volatile("cp.async.bulk.wait_group 0;" ::: "memory");
          asm volatile("st.relaxed.gpu.global.u32 [%0], %1;" :: "l"(&g_fO[j][seg][h]), "r"(epoch + 1) : "memory");
        } else {
          mbar_expect(sb + B_V, 10240);
        }
      }
      asm volatile("cp.async.bulk.wait_group 0;" ::: "memory");
    }
  } else if (w == 2) {
#pragma unroll 1
    for (int s = 0; s < NSTEP - 1; s++) {
      mbar_wait(sb + B_W3, s & 1);
      if (lane == 0) mbar_expect(sb + B_OM, j < 2 ? 2048 : 4096);
      mbar_wait(sb + B_MEM + 24, (s + 1) & 1);
      if (lane < 16) st_rlx(&g_acc[s ? (s - 1) & 3 : 4][(blockIdx.x * 2 + (lane >> 3)) * (AG / 4) + (lane & 7)], make_uint4(0, 0, 0, 0));
    }
  } else if (lane == 0) {
    const uint32_t so = sb & 0x1FFFFFF;
#pragma unroll 1
    for (int s = 0; s < NSTEP; s++) {
      mbar_wait(sb + B_ST, s & 1);
      if (j < 2) bulk_s2s(so + ((1 - j) << 25) + (j ? H_KB : H_QB), sb + H_ST, so + ((1 - j) << 25) + B_QK);
      else { bulk_s2s(so + H_VB, sb + H_QB, so + B_V); bulk_s2s(so + (1 << 25) + H_VB, sb + H_KB, so + (1 << 25) + B_V); }
    }
  }
  __syncwarp();
}

__global__ void __cluster_dims__(6, 1, 1) __launch_bounds__(512, 1)
h_kernel(const bf16* __restrict__ Wq, const bf16* __restrict__ Wk, const bf16* __restrict__ Wv, const bf16* __restrict__ Wo, const bf16* __restrict__ mem0,
         const bf16* __restrict__ x, const bf16* __restrict__ wqkv) {
  extern __shared__ __align__(1024) uint8_t smraw[];
  const uint32_t sb = smem_u32(smraw);
  const int j = (blockIdx.x % 6) >> 1, h = (blockIdx.x / 6) * 2 + (blockIdx.x & 1);
  const int tid = threadIdx.x, lane = tid & 31, w = __shfl_sync(~0u, (tid >> 5) & 3, 0), wg = __shfl_sync(~0u, tid >> 7, 0);
  asm volatile("griddepcontrol.launch_dependents;");
  const uint32_t epoch = *(volatile uint32_t*)&g_epoch;
  if (wg < 3) {
    const int u = (wg * 4 + w) * 96 + blockIdx.x;
    const bool wq = blockIdx.x < 72;
    if (wq) {
      for (int i = tid; i < 1728; i += 384) cp16(sb + H_WO + (i / 216) * 3472 + (i % 216) * 16, wqkv + (size_t)blockIdx.x * 8 * 1728 + i * 8);
    }
    const int useg = u / 18, urb = (u % 18) / 9, cp = u % 9;
    const uint32_t* p0 = (const uint32_t*)(x + (size_t)(useg * 32 + 2 * (lane >> 2) + urb) * 576) + cp * 32 + (lane & 3);
    uint32_t y[4][4];
#pragma unroll
    for (int i = 0; i < 4; i++) { y[i][0] = __ldg(p0 + i * 8); y[i][2] = __ldg(p0 + i * 8 + 4); y[i][1] = __ldg(p0 + i * 8 + 16 * 288); y[i][3] = __ldg(p0 + i * 8 + 16 * 288 + 4); }
    const int uc = wg * 4 + w;
    if (wq) {
      cp_wait_all();
      asm volatile("bar.sync 3, 384;" ::: "memory");
      if (uc < 11) {
        const uint32_t* p = (const uint32_t*)(smraw + H_WO + (lane >> 2) * 3472) + 27 * uc + (lane & 3);
        uint32_t wv[21];
#pragma unroll
        for (int i = 0; i < 21; i++) wv[i] = p[(i / 7) * 288 + (uc < 10 || i % 7 < 5 ? i % 7 : 0) * 4];
#pragma unroll
        for (int i = 0; i < 21; i++) g_wq[uc * 72 + blockIdx.x][i * 32 + lane] = wv[i];
        if (uc > 0) flag_add(&g_fWq[uc][0], lane);
      }
    }
    asm volatile("bar.arrive 4, 512;" ::: "memory");
#pragma unroll
    for (int i = 0; i < 4; i++) g_xa[0][useg][(urb * 36 + cp * 4 + i) * 32 + lane] = make_uint4(y[i][0], y[i][1], y[i][2], y[i][3]);
    const float4 s0 = row_stats<2>(&y[0]), s1 = row_stats<2>(&y[2]);
    if ((lane & 3) == 0) { *(float4*)&g_stA[0][useg][urb][2 * cp][lane >> 2] = s0; *(float4*)&g_stA[0][useg][urb][2 * cp + 1][lane >> 2] = s1; }
    flag_add(&g_fXA[0][useg][urb][0], lane);
    if (wq && uc == 0) hint_add(&g_fWq[0][0], lane);
  } else {
    const int t = tid - 384;
    if (HD > 0) { const uint32_t c0 = clock(); while ((uint32_t)clock() - c0 + 1 < HD + 1) {} }
    {
      const int c = t & 15;
      const bf16* src = (j == 0 ? Wq : j == 1 ? Wk : Wv) + h * 128 + (size_t)(t >> 4) * 4096 + c * 8;
#pragma unroll 1
      for (int kk = t >> 4; kk < 576; kk += 8, src += 8 * 4096) {
        cp16(kk < KR * 16 ? sb + kk * 272 + c * 16 : sb + H_WL + c * WLS + (kk - KR * 16) * 16, src);
        asm volatile("cp.async.commit_group; cp.async.wait_group %0;" :: "n"(HP) : "memory");
      }
    }
    asm volatile("bar.sync 4, 512;" ::: "memory");
    if (t < 96) {
      const int n = t % 24;
      const bf16* src = Wo + (size_t)(h * 128 + t / 24) * 576 + (18 * (n / 6) + 6 * j + n % 6) * 8;
#pragma unroll 1
      for (int d = t / 24; d < 128; d += 4, src += 4 * 576) {
        cp16(sb + H_WO + ((d & 96) + ((d >> 1) & 3) * 8 + ((d >> 3) & 3) * 2 + (d & 1)) * 400 + n * 16, src);
        asm volatile("cp.async.commit_group; cp.async.wait_group %0;" :: "n"(HP) : "memory");
      }
    }
  }
  {
    if (tid == 0) {
      for (int c = 0; c < 4; c++) mbar_init(sb + B_MEM + c * 8, ARM ? 4 : 1);
      mbar_init(sb + B_XT, 1); mbar_init(sb + B_XA, 1); mbar_init(sb + B_WS, 1); mbar_init(sb + B_XC, 8); mbar_init(sb + B_TD, 8); mbar_init(sb + B_XB, 1); mbar_init(sb + B_MD, 8); mbar_init(sb + B_ST, 8);
      mbar_init(sb + B_QK, 9); mbar_init(sb + B_V, 1); mbar_init(sb + B_OM, j < 2 ? 2 : 1); mbar_init(sb + B_OS, 2);
      mbar_init(sb + B_W2, 1); mbar_init(sb + B_W3, 4);
      mbar_expect(sb + B_QK, 10240); mbar_expect(sb + B_V, 10240);
      mbar_expect(sb + B_OM, j < 2 ? 2048 : 4096);
      asm volatile("fence.mbarrier_init.release.cluster;" ::: "memory");
    }
    cp_wait_all();
    fence_async();
    __syncthreads();
  }
  if (wg < 2) {
    asm volatile("setmaxnreg.inc.sync.aligned.u32 192;");
    if (j == 0) h_proj<0>(sb, wg, w, lane); else if (j == 1) h_proj<1>(sb, wg, w, lane); else h_proj<2>(sb, wg, w, lane);
    cluster_sync();
  } else if (wg == 2) {
    asm volatile("setmaxnreg.dec.sync.aligned.u32 104;");
    if (j == 0) h_chain<0>(smraw, sb, w, lane, epoch, mem0); else if (j == 1) h_chain<1>(smraw, sb, w, lane, epoch, mem0); else h_chain<2>(smraw, sb, w, lane, epoch, mem0);
    cluster_sync();
  } else {
    asm volatile("setmaxnreg.dec.sync.aligned.u32 24;");
    h_help(sb, h, j, w, lane, epoch);
    cluster_sync();
  }
}

#define XA_ON true
constexpr int G_W = 21, G_AQ = 11, G_AO = 4;
constexpr uint32_t G_SMEM = 232448;

template<int N, int NK, bool TWO, class F> __device__ __forceinline__ uint32_t gemm_rs(float* acc, const uint4* pa, uint32_t baddr, uint32_t tag, F&& ready) {
  constexpr int B1 = 6, B3 = N == 192 ? 23 : 30, B2 = N == 192 ? 14 : 16;
  uint32_t a[B3 * 4];
  constexpr int KS = N == 168 ? N * 2 : 384;
  const uint64_t bd = N == 168 ? mkdesc(baddr, N * 16, 128) : mkdesc(baddr, 1024, 3072) | (1ull << 62);
  uint32_t bad = 0;
  auto steps = [&](int k0, int k1) {
#pragma unroll
    for (int kk = k0; kk < k1; kk++) {
      const int slot = kk % B3;
      if (N == 192) { if (kk == 0) rs192t<0>(acc, &a[0], bd); else rs192t<1>(acc, &a[slot * 4], bd + kk * KS); }
      if (N == 168) { if (kk == 0) rs168t<0>(acc, &a[0], bd); else rs168t<1>(acc, &a[slot * 4], bd + kk * KS); }
      if (N == 144) rs144t<1>(acc, &a[slot * 4], bd + kk * KS);
    }
    wg_commit();
  };
  auto check = [&](int s0, int s1) {
#pragma unroll
    for (int i = s0; i < s1; i++) {
      asm volatile("lop3.b32 %0, %0, %1, %2, 0xF6;" : "+r"(bad) : "r"(a[i * 4]), "r"(tag));
      if (TWO) asm volatile("lop3.b32 %0, %0, %1, %2, 0xF6;" : "+r"(bad) : "r"(a[i * 4 + 2]), "r"(tag));
    }
  };
#pragma unroll
  for (int i = 0; i < B3; i++) ld_rlx(&a[i * 4], pa + i * 32);
  asm volatile("{.reg .pred p; setp.eq.u32 p, %0, 77; @p bar.sync 15, 32;}" :: "r"((uint32_t)(size_t)pa) : "memory");
  ready(0);
  auto refill = [&](int s0, int s1) {
    check(s0, s1);
    pa -= bad & (tag >> 2);
#pragma unroll
    for (int i = s0; i < s1; i++) ld_rlx(&a[i * 4], pa + (B3 + i) * 32);
    asm volatile("{.reg .pred p; setp.eq.u32 p, %0, 77; @p bar.sync 15, 32;}" :: "r"((uint32_t)(size_t)pa) : "memory");
  };
  wg_fence(); steps(0, B1);
  wg_fence(); steps(B1, B1 + GQ);
  wg_wait<1>(); refill(0, B1);
  ready(1);
  wg_fence(); steps(B1 + GQ, B2);
  if (NK - B3 > B1) {
    wg_fence(); steps(B2, B2 + GQ);
    wg_wait<1>(); refill(B1, B2);
    wg_fence(); steps(B2 + GQ, B3);
  } else {
    wg_fence(); steps(B2, B3);
  }
  wg_fence(); steps(B3, NK);
  wg_wait<1>();
  check(NK - B3, B3);
  wg_wait<0>();
  pin<N / 2>(acc);
  check(0, NK == 37 ? 34 - B3 : NK - B3);
  if (NK == 37 && !(tag & 2)) check(34 - B3, 37 - B3);
  return bad;
}
template<int ID> __device__ __forceinline__ void turn_wait(int wg, bool on) {
  asm volatile("{.reg .pred p, q; setp.eq.u32 p, %0, 0; setp.eq.u32 q, %0, 1; @p bar.sync %1, 256; @q bar.sync %2, 256;}" :: "r"(on ? wg : 2), "n"(ID), "n"(ID + 1) : "memory");
}
template<int ID> __device__ __forceinline__ void turn_pass(int wg, bool on) {
  asm volatile("{.reg .pred p, q; setp.eq.u32 p, %0, 0; setp.eq.u32 q, %0, 1; @p bar.arrive %2, 256; @q bar.arrive %1, 256;}" :: "r"(on ? wg : 2), "n"(ID), "n"(ID + 1) : "memory");
}
__device__ __forceinline__ bool wg_any(bool p, int wg) {
  uint32_t r;
  asm volatile("{.reg .pred p, q; setp.ne.u32 p, %1, 0; bar.red.or.pred q, %2, 128, p; selp.u32 %0, 1, 0, q;}" : "=r"(r) : "r"((uint32_t)p), "r"(6 + wg) : "memory");
  return __any_sync(~0u, r);
}

template<int NC> __device__ __forceinline__ void load_b(uint32_t sb, const bf16* __restrict__ src, int nrow) {
  constexpr int RP = 256 / NC;
  const int c = threadIdx.x % NC, r0 = threadIdx.x / NC;
  if (r0 < RP) {
    const bf16* p = src + r0 * 576 + c * 8;
#pragma unroll 2
    for (int r = r0; r < nrow; r += RP, p += RP * 576) cp16(sb + (r >> 3) * 3072 + (c >> 3) * 1024 + (r & 7) * 128 + ((c ^ r) & 7) * 16, p);
  }
}

__device__ __forceinline__ void role_W(uint32_t sb, int c, uint32_t epoch, const bf16* __restrict__ Wo, uint32_t zero) {
  const int tid = threadIdx.x, lane = tid & 31, w = __shfl_sync(~0u, (tid >> 5) & 3, 0), wg = __shfl_sync(~0u, tid >> 7, 0);
  const int ks = c / 3, ns = c % 3, k0 = ks * 37;
  { const uint32_t c0 = clock(); while ((uint32_t)clock() - c0 < WD) {} }
  GT(79, 2);
  {
    const int nblk = min(74, 512 - 2 * k0);
    load_b<24>(sb, Wo + (size_t)k0 * 16 * 576 + ns * 192, nblk * 8);
    for (int i = nblk * 192 + tid; i < 74 * 192; i += 256) sts4(sb + i * 16, 0, 0, 0, 0);
    cp_wait_all();
  }
  fence_async();
  asm volatile("bar.sync 1, 256;" ::: "memory");
  GT(79, 0);
  const int L = w >> 1, rb = w & 1;
#pragma unroll 1
  for (int s = wg; s < NSTEP; s += 2) {
    const int seg = s - L * LAG;
    const bool on = (uint32_t)seg < (uint32_t)NSEG;
    float acc[96];
    if (on) hint_wait(&g_fO[L][seg][min((k0 >> 3) + min(lane, 5), min((k0 + 36) >> 3, 31))], epoch + 1);
    GT(s, 0);
    const uint32_t tag = PRING == NSEG ? (epoch + 1) & 1 : ((seg / PRING) + 1) & 1;
    {
      uint32_t bad, it = 0;
      do {
        bad = gemm_rs<192, 37, false>(acc, &g_O[0][0][0][0][0] + (uint32_t)((((L * ORING + (seg & (ORING - 1))) * 2 + rb) * 256 + k0) * 32 + lane), sb, tag | (ks == 6 ? 2 : 0) | zero, [&](int p) { if (p == 0) turn_wait<2>(wg, s > 0 && it == 0); });
        if (++it > 100000) __trap();
      } while (XA_ON && wg_any(on && (bad & 1), wg));
      turn_pass<2>(wg, s < NSTEP - 1);
      REDO(0);
    }
    GT(s, 1);
    if (on) {
      if (L && s < NSEG) __nanosleep(PSD);
      uint4* const pp = &g_P[L][seg & (PRING - 1)][ks][rb][ns * 12][lane];
#pragma unroll
      for (int i = 0; i < 12; i++)
        st_rlx(pp + i * 32, make_uint4(pk_tag(acc[8 * i], acc[8 * i + 1], tag), pk(acc[8 * i + 2], acc[8 * i + 3]), pk(acc[8 * i + 4], acc[8 * i + 5]), pk(acc[8 * i + 6], acc[8 * i + 7])));
      hint_add(&g_fP[L][seg][rb][ns][0], lane);
    }
  }
}

__device__ __forceinline__ void role_R(uint32_t xch, int cg, uint32_t epoch, bf16* __restrict__ out) {
  const int lane = threadIdx.x & 31, w = __shfl_sync(~0u, (threadIdx.x >> 5) & 3, 0);
  const int rb = w >> 1, kk = 2 * cg + (w & 1);
  uint32_t v[7][4];
  auto fetch = [&](int L, int seg) {
    const uint4* const pp = &g_P[L][seg & (PRING - 1)][0][rb][kk][lane];
#pragma unroll
    for (int k = 0; k < 7; k++) ld_rlx(v[k], pp + k * 2304);
  };
  auto sum = [&](int L, int seg, uint32_t* y) {
    const uint32_t tag = PRING == NSEG ? (epoch + 1) & 1 : ((seg / PRING) + 1) & 1;
    uint32_t it = 1;
    while (true) {
      uint32_t bad = 0;
#pragma unroll
      for (int k = 0; k < 7; k++) bad |= v[k][0] ^ tag;
      if (__all_sync(~0u, (bad & 1) == 0)) break;
      if (++it > SPIN_MAX) __trap();
      fetch(L, seg);
    }
    REDO(3);
#pragma unroll
    for (int r = 0; r < 4; r++) {
      const float lo = ((blo(v[0][r]) + blo(v[1][r])) + (blo(v[2][r]) + blo(v[3][r]))) + ((blo(v[4][r]) + blo(v[5][r])) + (blo(v[6][r]) + blo(y[r])));
      const float hi = ((bhi(v[0][r]) + bhi(v[1][r])) + (bhi(v[2][r]) + bhi(v[3][r]))) + ((bhi(v[4][r]) + bhi(v[5][r])) + (bhi(v[6][r]) + bhi(y[r])));
      y[r] = (r == 0 && L == 0) ? pk_tag(lo, hi, (epoch + 1) & 1) : pk(lo, hi);
    }
  };
#pragma unroll 1
  for (int s = 0; s < NSTEP; s++) {
    const bool on0 = s < NSEG, on1 = s >= LAG;
    const int s0 = on0 ? s : NSEG - 1, s1 = on1 ? s - LAG : 0;
    uint32_t y[2][4];
    if (XA_ON) flag_wait((lane & 1) && on1 ? &g_fXB[1][s1][0] : &g_fXB[0][s0][0], (epoch + 1) * 8);
#pragma unroll
    for (int i = 0; i < 8; i++)
      asm volatile("ld.relaxed.gpu.global.u32 %0, [%1];" : "=r"(y[i >> 2][i & 3])
                   : "l"((const uint32_t*)&g_xb[i >> 2][i >> 2 ? s1 : s0][0] + (rb * 144 + kk * 2) * 32 + lane + (i & 1) * 2304 + ((i >> 1) & 1) * 32) : "memory");
    hint_wait(on0 ? &g_fP[0][s0][rb][cg / 6][0] : &g_fP[1][s1][rb][cg / 6][0], (epoch + 1) * 7);
    if (on0) {
      fetch(0, s0);
      sum(0, s0, y[0]);
      GTR(s, 2);
      st_rlx(&g_xa[1][s0][(rb * 36 + kk) * 32 + lane], make_uint4(y[0][0], y[0][1], y[0][2], y[0][3]));
      hint_add(&g_fXA[1][s0][rb][0], lane);
    }
    if (on1) fetch(1, s1);
    if (on0) {
      const float4 a = row_stats<1>(y);
      const uint32_t xa = xch + ((s & 1) * 2 + rb) * 128 + (lane >> 2) * 16;
      if ((w & 1) && (lane & 3) == 0) sts4(xa, __float_as_uint(a.x), __float_as_uint(a.y), __float_as_uint(a.z), __float_as_uint(a.w));
      asm volatile("bar.sync %0, 64;" :: "r"(10 + rb) : "memory");
      if (!(w & 1)) {
        const float4 o = lds_f4(xa);
        const float q0 = a.y + o.y + 8.f * (a.x - o.x) * (a.x - o.x), q1 = a.w + o.w + 8.f * (a.z - o.z) * (a.z - o.z);
        const uint32_t tag = (epoch + 1) & 1;
        if ((lane & 3) == 0)
          st_rlx(&g_stA[1][s0][rb][cg][lane >> 2], make_uint4(__float_as_uint(0.5f * (a.x + o.x)), (__float_as_uint(q0) & ~1u) | tag, __float_as_uint(0.5f * (a.z + o.z)), (__float_as_uint(q1) & ~1u) | tag));
      }
      GTR(s, 3);
    }
    if (on1) {
      sum(1, s1, y[1]);
      uint32_t* po = (uint32_t*)(out + (size_t)(s1 * 32 + 2 * (lane >> 2) + rb) * 576) + kk * 8 + (lane & 3);
      po[0] = y[1][0]; po[4] = y[1][2]; po[16 * 288] = y[1][1]; po[16 * 288 + 4] = y[1][3];
      GTR(78, 3);
    }
  }
  if (cg == 0 && threadIdx.x == 256) g_epoch = epoch + 1;
}

constexpr uint32_t AQ_KV = 193536, AQ_Q = AQ_KV + 4 * 24 * 304, AQ_ST = AQ_KV + 48 * 304 + 288;

__device__ __forceinline__ void role_AS(uint32_t sb, uint32_t epoch) {
  const int lane = threadIdx.x & 31, w = __shfl_sync(~0u, (threadIdx.x >> 5) & 3, 0);
  const int st = w >> 1, rb = w & 1, hf = lane >> 4;
  const uint32_t tag = (epoch + 1) & 1;
#pragma unroll 1
  for (int n = 0; n < NSEG + LEAD; n++) {
    const int seg = n - st * LEAD;
    float mean = 0.f, rs = 0.f;
    if ((uint32_t)seg < (uint32_t)NSEG) {
      if (st) hint_wait(&g_fXA[1][seg][rb][0], (epoch + 1) * 36); else if (XA_ON) flag_wait(&g_fXA[0][seg][rb][0], (epoch + 1) * 9);
      const float2* ps = (const float2*)&g_stA[st][seg][rb][hf * 9][0] + (lane & 15);
      float m[9], q[9];
      uint32_t it = 0;
      while (true) {
        uint32_t bad = 0;
#pragma unroll
        for (int i = 0; i < 9; i++) {
          asm volatile("ld.relaxed.gpu.global.v2.f32 {%0,%1}, [%2];" : "=f"(m[i]), "=f"(q[i]) : "l"(ps + i * 16) : "memory");
        }
#pragma unroll
        for (int i = 0; i < 9; i++) bad |= __float_as_uint(q[i]) ^ tag;
        if (!st || __all_sync(~0u, (bad & 1) == 0)) break;
        if (++it > SPIN_MAX) __trap();
      }
#pragma unroll
      for (int i = 0; i < 9; i++) mean += m[i];
      mean = (mean + __shfl_xor_sync(~0u, mean, 16)) * (-1.f / 18);
#pragma unroll
      for (int i = 0; i < 9; i++) rs += q[i] + 32.f * (m[i] + mean) * (m[i] + mean);
      rs = rsqrtf((rs + __shfl_xor_sync(~0u, rs, 16)) * (1.f / 576) + 1e-5f);
    }
    asm volatile("bar.sync 11, 256;" ::: "memory");
    if (lane < 16) asm volatile("st.shared.v2.f32 [%0], {%1,%2};" :: "r"(sb + AQ_ST + (w * 8 + (lane >> 1)) * 304 + (lane & 1) * 8), "f"(mean), "f"(rs) : "memory");
    asm volatile("bar.arrive 10, 256;" ::: "memory");
  }
}

__device__ __forceinline__ void role_AQ(uint32_t sb, int c, uint32_t epoch, uint32_t zero) {
  const int tid = threadIdx.x, lane = tid & 31, w = __shfl_sync(~0u, (tid >> 5) & 3, 0), wg = __shfl_sync(~0u, tid >> 7, 0);
  {
    const uint32_t mb = sb + G_SMEM - 8;
    if (tid < 32) {
      if (lane == 0) { mbar_init(mb, 1); fence_async(); mbar_expect(mb, AQ_KV); }
      if (XA_ON) flag_wait(&g_fWq[c][0], (epoch + 1) * 72);
      asm volatile("fence.proxy.async.global;" ::: "memory");
      GT(79, 2);
      if (lane < 8) bulk_g2s(sb + lane * 24192, &g_wq[c * 72 + lane * 9][0], 24192, mb);
    }
    for (int i = tid; i < 1152; i += 256) st_rlx(&g_ones[i], make_uint4(0x3F803F80u, 0x3F803F80u, 0x3F803F80u, 0x3F803F80u));
    for (int i = tid; i < (4 * 24 * 304 + 4 * 16 * 144 + 384) / 16; i += 256) sts4(sb + AQ_KV + i * 16, 0, 0, 0, 0);
    asm volatile("bar.sync 1, 256;" ::: "memory");
    mbar_wait(mb, 0);
  }
  fence_async();
  asm volatile("bar.sync 1, 256;" ::: "memory");
  GT(79, 0);
  const int st = w >> 1, rb = w & 1;
  const uint32_t kvb = sb + AQ_KV + w * 24 * 304, qb = sb + AQ_Q + w * 16 * 144;
  if (wg == 0) asm volatile("bar.arrive 11, 256;" ::: "memory");
  const uint32_t rsb = sb + AQ_Q + 4 * 16 * 144 + w * 96;
  const uint32_t tag = (epoch + 1) & 1;
#pragma unroll 1
  for (int n = wg; n < NSEG + LEAD; n += 2) {
    const int seg = n - st * LEAD;
    const bool on = (uint32_t)seg < (uint32_t)NSEG;
    float acc[84];
    int lane = lane_id(), g = lane >> 2, q = lane & 3;
    if (on) { if (st) hint_wait(&g_fXA[1][seg][rb][0], (epoch + 1) * 36); else if (XA_ON) flag_wait(&g_fXA[0][seg][rb][0], (epoch + 1) * 9); }
    GT(n, 0);
    {
      uint32_t bad, it = 0;
      do {
        bad = gemm_rs<168, 36, false>(acc, on ? &g_xa[st][seg][rb * 36 * 32 + lane] : &g_ones[lane], sb, tag | zero, [&](int p) {
          if (p == 0) turn_wait<2>(wg, n > 0 && it == 0);
          if (p == APS) turn_wait<8>(wg, n > 0 && it == 0);
        });
        if (++it > 100000) __trap();
      } while (XA_ON && wg_any(on && st && (bad & 1), wg));
      turn_pass<2>(wg, n < NSEG + LEAD - 1);
      REDO(1);
    }
    GT(n, 1);
    lane = lane_id(); g = lane >> 2; q = lane & 3;
    const uint32_t csa = sb + AQ_KV + 288 + (q >> 1) * 304 + (q & 1) * 8;
    asm volatile("bar.sync 10, 256;" ::: "memory");
    const float4 sq = lds_f4(sb + AQ_ST + (w * 8 + g) * 304);
    const float mean0 = sq.x, rs0 = sq.y, mean1 = sq.z, rs1 = sq.w;
    if (n == 0) {
      if (w == 2 && g == 0) {
#pragma unroll
        for (int jn = 0; jn < 21; jn++) asm volatile("st.shared.v2.f32 [%0], {%1,%2};" :: "r"(csa + jn * 608), "f"(acc[4 * jn]), "f"(acc[4 * jn + 1]) : "memory");
      }
      asm volatile("bar.sync 4, 128;" ::: "memory");
    }
    auto release = [&](uint32_t z) {
      turn_pass<8>(wg + z, n < NSEG + LEAD - 1);
      asm volatile("{.reg .pred p; setp.ne.u32 p, %0, 0; @p bar.arrive 11, 256;}" :: "r"((uint32_t)(n < NSEG + LEAD - 1)) : "memory");
    };
    if (on) {
      const uint32_t pos0 = (2 * n) % 3, pos1 = (2 * n + 1) % 3, pos2 = (2 * n + 2) % 3;
      const uint32_t aq = qb + g * 144 + 4 * q, alo = kvb + (pos1 * 8 + g) * 304 + 4 * q, ahi = kvb + (pos2 * 8 + g) * 304 + 4 * q;
      const uint32_t e2 = q >= 1 ? 12 : 0, e4 = q >= 2 ? 12 : 0;
      float cs_[21][2];
#pragma unroll
      for (int jn = 0; jn < 21; jn++) asm volatile("ld.shared.v2.f32 {%0,%1}, [%2];" : "=f"(cs_[jn][0]), "=f"(cs_[jn][1]) : "r"(csa + jn * 608));
      if (q < 2) sts1(rsb + (q ? pos2 : pos1) * 32 + g * 4, __float_as_uint(q ? rs1 : rs0));
#pragma unroll
      for (int jn = 0; jn < 21; jn++) {
        const int part = jn / 7, b7 = jn % 7;
        const uint32_t co = 16 * b7 + (b7 > 2 ? 12 : 0) + (b7 > 4 ? 12 : 0), ex = b7 == 2 ? e2 : b7 == 4 ? e4 : 0;
        const uint32_t lo = (part == 0 ? aq : alo + (part - 1) * 144) + co + ex;
        const uint32_t hi = (part == 0 ? aq + 8 * 144 : ahi + (part - 1) * 144) + co + ex;
        const float c0 = cs_[jn][0], c1 = cs_[jn][1];
        const uint32_t keep = (jn == 6 && q == 3) ? 0u : ~0u;
        sts1(lo, pk(fmaf(mean0, c0, acc[4 * jn]), fmaf(mean0, c1, acc[4 * jn + 1])) & keep);
        sts1(hi, pk(fmaf(mean1, c0, acc[4 * jn + 2]), fmaf(mean1, c1, acc[4 * jn + 3])) & keep);
      }
      __syncwarp();
      const bool e0 = 2 * q <= g, e1 = 2 * q + 1 <= g;
      float ra0, ra1, rb0, rb1;
      asm volatile("ld.shared.f32 %0, [%1];" : "=f"(ra0) : "r"(rsb + (e0 ? pos1 : pos0) * 32 + q * 8) : "memory");
      asm volatile("ld.shared.f32 %0, [%1];" : "=f"(ra1) : "r"(rsb + (e1 ? pos1 : pos0) * 32 + q * 8 + 4) : "memory");
      asm volatile("ld.shared.f32 %0, [%1];" : "=f"(rb0) : "r"(rsb + (e0 ? pos2 : pos1) * 32 + q * 8) : "memory");
      asm volatile("ld.shared.f32 %0, [%1];" : "=f"(rb1) : "r"(rsb + (e1 ? pos2 : pos1) * 32 + q * 8 + 4) : "memory");
      const float cs = 0.23570226039551584f * 1.4426950408889634f;
      const float fa0 = ra0 * rs0 * cs, fa1 = ra1 * rs0 * cs, fb0 = rb0 * rs1 * cs, fb1 = rb1 * rs1 * cs;
      const float na0 = (e0 || seg > 0) ? 0.f : -INFINITY, na1 = (e1 || seg > 0) ? 0.f : -INFINITY;
      const uint32_t mk = (e0 ? 0xFFFFu : 0u) | (e1 ? 0xFFFF0000u : 0u);
      const uint32_t ka = kvb + (lane & 7) * 304 + min(lane >> 3, 2) * 16;
      const uint32_t vb = kvb + (lane & 7) * 304 + 144, p01 = ((lane & 8) ? pos1 : pos0) * 2432, va2 = vb + pos2 * 2432 + 32;
      const uint32_t va0 = vb + p01 + (lane >> 4) * 16, va1 = lane < 16 ? vb + p01 + 32 : vb + pos2 * 2432 + (lane & 8) * 2;
      float a0[3], a1[3], b0[3], b1[3];
      uint32_t vf[3][9];
#pragma unroll
      for (int lh = 0; lh < 3; lh++) {
        uint32_t qa[4], qc[2], kf[3][4];
        ldsm4(qa, qb + (lane & 15) * 144 + (lane >> 4) * 16 + lh * 48);
        ldsm2(qc, qb + (lane & 15) * 144 + 32 + lh * 48);
        ldsm4(kf[0], ka + pos0 * 2432 + lh * 48); ldsm4(kf[1], ka + pos1 * 2432 + lh * 48); ldsm4(kf[2], ka + pos2 * 2432 + lh * 48);
        float sc[3][4];
#pragma unroll
        for (int b = 0; b < 3; b++) {
          sc[b][0] = sc[b][1] = sc[b][2] = sc[b][3] = 0.f;
          HMMA(sc[b], qa[0], qa[1], qa[2], qa[3], kf[b][0], kf[b][1]);
          HMMA8(sc[b], qc[0], qc[1], kf[b][2]);
        }
        a0[lh] = fmaf(e0 ? sc[1][0] : sc[0][0], fa0, na0); a1[lh] = fmaf(e1 ? sc[1][1] : sc[0][1], fa1, na1);
        b0[lh] = (e0 ? sc[2][2] : sc[1][2]) * fb0; b1[lh] = (e1 ? sc[2][3] : sc[1][3]) * fb1;
      }
#pragma unroll
      for (int lh = 0; lh < 3; lh++) {
        ldsm4t(&vf[lh][0], va0 + lh * 48); ldsm4t(&vf[lh][4], va1 + lh * 48);
        asm volatile("ldmatrix.sync.aligned.m8n8.x1.trans.shared.b16 {%0}, [%1];" : "=r"(vf[lh][8]) : "r"(va2 + lh * 48) : "memory");
      }
      float m0[3], m1[3];
#pragma unroll
      for (int lh = 0; lh < 3; lh++) { m0[lh] = fmaxf(a0[lh], a1[lh]); m1[lh] = fmaxf(b0[lh], b1[lh]); }
#pragma unroll
      for (int o = 1; o < 4; o *= 2)
#pragma unroll
        for (int lh = 0; lh < 3; lh++) { m0[lh] = fmaxf(m0[lh], __shfl_xor_sync(~0u, m0[lh], o)); m1[lh] = fmaxf(m1[lh], __shfl_xor_sync(~0u, m1[lh], o)); }
      float o_[3][3][4];
#pragma unroll
      for (int lh = 0; lh < 3; lh++) {
        a0[lh] = ex2(a0[lh] - m0[lh]); a1[lh] = ex2(a1[lh] - m0[lh]); b0[lh] = ex2(b0[lh] - m1[lh]); b1[lh] = ex2(b1[lh] - m1[lh]);
        m0[lh] = a0[lh] + a1[lh]; m1[lh] = b0[lh] + b1[lh];
        const uint32_t pa = pk(a0[lh] * ra0, a1[lh] * ra1), pb = pk(b0[lh] * rb0, b1[lh] * rb1);
        const uint32_t f0 = pa & ~mk, z0 = pa & zero, f2 = pa & mk, f3 = pb & ~mk, z1 = pb & zero, f5 = pb & mk;
#pragma unroll
        for (int cb = 0; cb < 3; cb++) {
          float* o = o_[lh][cb];
          o[0] = o[1] = o[2] = o[3] = 0.f;
          HMMA(o, f0, z0, f2, f3, vf[lh][2 * cb], vf[lh][2 * cb + 1]);
          HMMA8(o, z1, f5, vf[lh][6 + cb]);
        }
      }
#pragma unroll
      for (int o = 1; o < 4; o *= 2)
#pragma unroll
        for (int lh = 0; lh < 3; lh++) { m0[lh] += __shfl_xor_sync(~0u, m0[lh], o); m1[lh] += __shfl_xor_sync(~0u, m1[lh], o); }
      uint32_t dn = zero;
#pragma unroll
      for (int i = 0; i < 9; i++) dn &= __float_as_uint(o_[i / 3][i % 3][0]);
      release(dn);
      const uint8_t* po = (const uint8_t*)&g_oA[st][seg][rb * 36 * 32 + g * 4];
#pragma unroll
      for (int lh = 0; lh < 3; lh++) {
        const float s0 = rcp(m0[lh]), s1 = rcp(m1[lh]);
        const uint32_t col = 54 * c + 18 * lh + 2 * q, o0 = (col >> 4) * 512 + (col & 6) * 8 + (col & 8), o1 = (col & 8) ? o0 + 504 : o0 + 8;
#pragma unroll
        for (int cb = 0; cb < 3; cb++)
          asm volatile("{.reg .pred p; setp.ne.u32 p, %3, 0; @p st.relaxed.gpu.global.v2.b32 [%0], {%1,%2};}"
                       :: "l"(po + (cb == 1 ? o1 : o0) + (cb == 2 ? 512 : 0)), "r"(pk_tag(o_[lh][cb][0] * s0, o_[lh][cb][1] * s0, tag)), "r"(pk(o_[lh][cb][2] * s1, o_[lh][cb][3] * s1)),
                          "r"((uint32_t)(col < 576 && (cb < 2 || q == 0))) : "memory");
      }
      hint_add(&g_fOA[st][seg][rb][0], lane);
    } else {
      release(0);
    }
    GT(n, 2);
  }
}

__device__ __forceinline__ void role_AO(uint8_t* smraw, uint32_t sb, int c, uint32_t epoch, const bf16* __restrict__ wo, uint32_t zero) {
  const int tid = threadIdx.x, lane = tid & 31, w = __shfl_sync(~0u, (tid >> 5) & 3, 0), wg = __shfl_sync(~0u, tid >> 7, 0);
  load_b<18>(sb, wo + c * 144, 576);
  cp_wait_all();
  fence_async();
  asm volatile("bar.sync 1, 256;" ::: "memory");
  GT(79, 0);
  const int st = w >> 1, rb = w & 1, g = lane >> 2, q = lane & 3;
  const uint32_t tag = (epoch + 1) & 1;
#pragma unroll 1
  for (int n = wg; n < NSEG + LEAD; n += 2) {
    const int seg = n - st * LEAD;
    const bool on = (uint32_t)seg < (uint32_t)NSEG;
    float acc[72];
    if (on) { if (st) hint_wait(&g_fXA[1][seg][rb][0], (epoch + 1) * 36); else if (XA_ON) flag_wait(&g_fXA[0][seg][rb][0], (epoch + 1) * 9); }
    {
      uint32_t bad, it = 0;
      do {
        uint32_t br = 0;
        {
          uint32_t res[9][4];
#pragma unroll
          for (int i = 0; i < 9; i++) ld_rlx(res[i], &g_xa[st][on ? seg : 0][(rb * 36 + c * 9) * 32 + lane] + i * 32);
#pragma unroll
          for (int i = 0; i < 36; i++) { acc[2 * i] = blo(res[i >> 2][i & 3]); acc[2 * i + 1] = bhi(res[i >> 2][i & 3]); }
#pragma unroll
          for (int i = 0; i < 9; i++) br |= res[i][0] ^ tag;
          pin<72>(acc); OPAQUE(br);
        }
        if (on) hint_wait(&g_fOA[st][seg][rb][0], (epoch + 1) * G_AQ);
        GT(n, 0);
        bad = gemm_rs<144, 36, true>(acc, &g_oA[st][on ? seg : 0][rb * 36 * 32 + lane], sb, tag | zero, [&](int p) { if (p == 0) turn_wait<2>(wg, n > 0 && it == 0); });
        if (st) bad |= br;
        if (++it > 100000) __trap();
      } while (wg_any(on && (bad & 1), wg));
      turn_pass<2>(wg, n < NSEG + LEAD - 1);
      REDO(2);
    }
    GT(n, 1);
    if (on) {
      uint32_t y[9][4];
      uint32_t* px = (uint32_t*)&g_xb[st][seg][0] + (rb * 144 + c * 18) * 32 + lane;
#pragma unroll
      for (int i = 0; i < 36; i++) {
        y[i >> 2][i & 3] = pk(acc[2 * i], acc[2 * i + 1]);
        px[(i >> 1) * 32 + (i & 1) * 2304] = y[i >> 2][i & 3];
      }
      const float4 a = row_stats<9>(y);
      if (q < 2) g_stB[st][seg][c][rb * 16 + q * 8 + g] = q ? make_float2(a.z, a.w) : make_float2(a.x, a.y);
      flag_add(&g_fXB[st][seg][0], lane);
    }
    GT(n, 2);
  }
}

__global__ void __launch_bounds__(384, 1)
g_kernel(const bf16* __restrict__ wo, const bf16* __restrict__ Wo, bf16* __restrict__ out, uint32_t zero) {
  extern __shared__ __align__(1024) uint8_t smraw[];
  const uint32_t sb = smem_u32(smraw);
  const uint32_t epoch = *(volatile uint32_t*)&g_epoch;
  const int b = blockIdx.x;
  GT(79, 1);
  const bool main_wg = __shfl_sync(~0u, threadIdx.x >> 8, 0) == 0;
  if (b < G_W) {
    if (main_wg) { asm volatile("setmaxnreg.inc.sync.aligned.u32 216;"); role_W(sb, b, epoch, Wo, zero); }
    else { asm volatile("setmaxnreg.dec.sync.aligned.u32 72;"); if (b < 18) role_R(sb + G_SMEM - 512, b, epoch, out); }
  } else if (main_wg) {
    asm volatile("setmaxnreg.inc.sync.aligned.u32 232;");
    if (b < G_W + G_AQ) role_AQ(sb, b - G_W, epoch, zero); else role_AO(smraw, sb, b - G_W - G_AQ, epoch, wo, zero);
  } else {
    asm volatile("setmaxnreg.dec.sync.aligned.u32 40;");
    if (b < G_W + G_AQ) role_AS(sb, epoch);
  }
}

extern "C" void kernel_launch(void* const* d_in, const int* in_sizes, int n_in, void* d_out, int out_size) {
  const bf16 *x = (const bf16*)d_in[0], *wqkv = (const bf16*)d_in[1], *wo = (const bf16*)d_in[2], *mem0 = (const bf16*)d_in[4];
  const bf16 *Wq = (const bf16*)d_in[5], *Wk = (const bf16*)d_in[6], *Wv = (const bf16*)d_in[7], *Wo = (const bf16*)d_in[8];
  cudaFuncSetAttribute(h_kernel, cudaFuncAttributeMaxDynamicSharedMemorySize, H_SMEM);
  cudaFuncSetAttribute(g_kernel, cudaFuncAttributeMaxDynamicSharedMemorySize, G_SMEM);
  cudaStream_t st = cudaStreamPerThread;
  h_kernel<<<96, 512, H_SMEM, st>>>(Wq, Wk, Wv, Wo, mem0, x, wqkv);
  cudaLaunchConfig_t cfg = {};
  cfg.gridDim = dim3(G_W + G_AQ + G_AO); cfg.blockDim = dim3(384); cfg.dynamicSmemBytes = G_SMEM; cfg.stream = st;
  cudaLaunchAttribute at[1];
  at[0].id = cudaLaunchAttributeProgrammaticStreamSerialization; at[0].val.programmaticStreamSerializationAllowed = 1;
  cfg.attrs = at; cfg.numAttrs = 1;
  cudaLaunchKernelEx(&cfg, g_kernel, wo, Wo, (bf16*)d_out, 0u);
}
```
